```python
import torch

def _softmax(x, axis=-1):
    return torch.softmax(x, dim=axis)

def _gelu(x):
    return torch.nn.functional.gelu(x, approximate='tanh')

def _silu(x):
    return torch.nn.functional.silu(x)

def _sigmoid(x):
    return torch.sigmoid(x)

def _layernorm(x, axis=-1, eps=1e-05):
    m = x.mean(dim=axis, keepdim=True)
    v = x.var(dim=axis, keepdim=True, unbiased=False)
    return (x - m) / torch.sqrt(v + eps)

def _scatter_add(tgt, idx, src, axis=0):
    return tgt.clone().index_add_(axis, idx, src)

def _segment_sum(src, seg, n):
    out = torch.zeros((n,) + src.shape[1:], dtype=src.dtype)
    return out.index_add_(0, seg, src)

def _pad(x, pw):
    flat = tuple((v for pair in reversed(pw) for v in pair))
    return torch.nn.functional.pad(x, flat)
kernel_name = 'adaLN_cond__linear_kernel_hedgehog__glu_gated_reglu__prompt'

def setup_inputs():

    _w = lambda a: (lambda t: t.to(torch.bfloat16) if t.is_floating_point() else t)(torch.as_tensor(a))

    def _A_setup():
        B, S, D, H = (1, 2048, 512, 32)
        Dh = D // H
        return {'x': _w((lambda *s: torch.randn(*s, dtype=torch.bfloat16) * 0.05)(B, S, D)), 'wqkv': _w((lambda *s: torch.randn(*s, dtype=torch.bfloat16) * 0.4)(D, 3 * D)), 'w_phi': _w((lambda *s: torch.randn(*s, dtype=torch.bfloat16) * 0.4)(H, Dh, Dh) * Dh ** (-0.5)), 'wo': _w((lambda *s: torch.randn(*s, dtype=torch.bfloat16) * 0.05)(D, D))}
    _A_in = _A_setup()

    def _B_setup():
        B, S, D, F = (1, 2048, 512, 1792)
        return {'x': _w((lambda *s: torch.randn(*s, dtype=torch.bfloat16) * 0.05)(B, S, D)), 'W_gate': _w((lambda *s: torch.randn(*s, dtype=torch.bfloat16) * 0.8)(D, F) * (2.0 / D) ** 0.5), 'W_up': _w((lambda *s: torch.randn(*s, dtype=torch.bfloat16) * 0.8)(D, F) * (2.0 / D) ** 0.5), 'W_down': _w((lambda *s: torch.randn(*s, dtype=torch.bfloat16) * 0.8)(F, D) * (1.0 / F) ** 0.5)}
    _B_in = _B_setup()
    return {'A_x': _A_in['x'], 'A_wqkv': _A_in['wqkv'], 'A_w_phi': _A_in['w_phi'], 'A_wo': _A_in['wo'], 'B_x': _B_in['x'], 'B_W_gate': _B_in['W_gate'], 'B_W_up': _B_in['W_up'], 'B_W_down': _B_in['W_down'], 'c': _w((lambda *s: torch.randn(*s, dtype=torch.bfloat16) * 0.2)(1, 512) * 8.0), 'w_mod': _w((lambda *s: torch.randn(*s, dtype=torch.bfloat16) * 0.2)(512, 6 * 512) * 512 ** (-0.5) * 8.0)}

def reference(A_x, A_wqkv, A_w_phi, A_wo, B_x, B_W_gate, B_W_up, B_W_down, c, w_mod):

    def _A_ref(x, wqkv, w_phi, wo):
        B, S, D = x.shape
        H = 32
        Dh = D // H
        qkv = (lambda x, *d: x.permute(*d))((x @ wqkv).reshape(B, S, 3, H, Dh), 2, 0, 3, 1, 4)
        q, k, v = (qkv[0], qkv[1], qkv[2])
        pq = torch.einsum('bhsd,hdf->bhsf', q, w_phi)
        pk = torch.einsum('bhsd,hdf->bhsf', k, w_phi)
        phi_q = torch.concatenate([_softmax(pq, axis=-1), _softmax(-pq, axis=-1)], axis=-1)
        phi_k = torch.concatenate([_softmax(pk, axis=-1), _softmax(-pk, axis=-1)], axis=-1)
        kv = torch.einsum('bhsf,bhsd->bhfd', phi_k, v)
        z = torch.einsum('bhsf->bhf', phi_k)
        num = torch.einsum('bhqf,bhfd->bhqd', phi_q, kv)
        den = torch.einsum('bhqf,bhf->bhq', phi_q, z)[..., None] + 1e-06
        o = num / den
        return (lambda x, *d: x.permute(*d))(o, 0, 2, 1, 3).reshape(B, S, D) @ wo

    def _B_ref(x, W_gate, W_up, W_down):
        gate = torch.einsum('bsd,df->bsf', x, W_gate)
        up = torch.einsum('bsd,df->bsf', x, W_up)
        gate = gate * (lambda x, dt: x.to(dt))(gate > 0, gate.dtype)
        h = gate * up
        return torch.einsum('bsf,fd->bsd', h, W_down)
    x = A_x
    mod = (_silu(c) @ w_mod).reshape(c.shape[0], 6, 1, -1)
    sa, ca, ga, sb, cb, gb = (mod[:, 0].clone(), mod[:, 1].clone(), mod[:, 2].clone(), mod[:, 3].clone(), mod[:, 4].clone(), mod[:, 5].clone())
    h = _layernorm(x, axis=-1) * (1 + ca) + sa
    x = x + ga * _A_ref(h, A_wqkv, A_w_phi, A_wo)
    h = _layernorm(x, axis=-1) * (1 + cb) + sb
    x = x + gb * _B_ref(h, B_W_gate, B_W_up, B_W_down)
    return x
```

```cpp
#include <cuda_runtime.h>
#include <cuda_bf16.h>
#include <cuda.h>
#include <stdint.h>

namespace {

constexpr int WDELAY = 2800;
constexpr int POLLK = 8;
constexpr int PF1 = 24;
constexpr int PIV = 1;
constexpr int GU = 4;
constexpr int GM = 32;
constexpr int WB1 = 3;
constexpr int NB = 3;
constexpr int NST = 6;
constexpr uint32_t SM_BASE = 1024;
constexpr uint32_t SM_A    = 0;
constexpr uint32_t SM_XS   = 65536;
constexpr uint32_t SM_KV   = SM_XS + 16384;
constexpr uint32_t SM_RING = 131072;
constexpr uint32_t SM_WPHI = SM_RING + 3 * 16384;
constexpr uint32_t SM_T1   = SM_WPHI + 8192;
constexpr uint32_t SM_SC   = SM_T1 + 2048;
constexpr uint32_t SM_RED  = SM_SC + 2048;
constexpr uint32_t SM_WM   = SM_RING + 4 * 16384;
constexpr uint32_t SM_GAB  = SM_RING + NST * 16384;
constexpr uint32_t SM_EPO  = SM_GAB + 1024;
constexpr uint32_t SM_BAR  = SM_EPO + 8;
constexpr uint32_t B_X     = SM_BAR;
constexpr uint32_t B_FULL  = B_X + 64;
constexpr uint32_t B_QFULL = B_FULL + 8 * NST;
constexpr uint32_t B_LAND  = B_QFULL + 32;
constexpr uint32_t B_AUX   = B_LAND + 128;
constexpr uint32_t B_EPO   = B_AUX + 8;
constexpr uint32_t B_MOD2  = B_EPO + 8;
constexpr uint32_t B_KVZ   = B_MOD2 + 8;
constexpr uint32_t B_MFREE = B_KVZ + 8;
constexpr uint32_t B_ZFREE = B_MFREE + 8;
constexpr uint32_t B_XFREE = B_ZFREE + 16;
constexpr uint32_t B_PUBKV = B_XFREE + 8;
constexpr uint32_t B_AFREE = B_PUBKV + 8;
constexpr uint32_t B_QDONE = B_AFREE + 8;
constexpr uint32_t B_DONE  = B_QDONE + 8;
constexpr uint32_t B_OFREE = B_DONE + 8;
constexpr uint32_t B_EMPTY = B_OFREE + 8;
constexpr uint32_t SM_END  = B_EMPTY + 8 * NST + 8;
constexpr uint32_t SMEM_BYTES = 232448;
static_assert(B_MOD2 == SM_BAR + 36 * 8 && SM_END == SM_BAR + 54 * 8, "barriers");
static_assert(SM_END <= SMEM_BYTES, "smem");

constexpr size_t G_MOD1  = 4096;
constexpr size_t G_MOD2  = G_MOD1 + 16384;
constexpr size_t G_KV    = G_MOD2 + 8192;
constexpr size_t G_RB    = 2097152;
constexpr size_t G_FL2   = 0;
constexpr size_t G_FL4   = 512;
constexpr size_t G_STAT  = 4096;
constexpr size_t G_O     = G_STAT + 8192;
constexpr size_t G_X1    = G_O + 131072;
constexpr size_t G_P     = G_X1 + 131072;
constexpr size_t G_HH    = G_P + 524288;
constexpr size_t G_END   = G_RB * 18;

__device__ __align__(1024) unsigned char g_scratch[G_END];

struct Maps { CUtensorMap qkv, wo, g1, u1, g2, u2, dA, dB, xs, wm, x; };

__host__ __device__ constexpr int piece_of(int i, int j) { return i == 0 ? j : (i <= j ? i - 1 : i); }

struct Sched { uint2 e[16][64]; };
constexpr Sched make_sched() {
    Sched t = {};
    for (int jr = 0; jr < 16; jr++) {
        const int j = jr >> 1, rank = jr & 1, i2 = j >> 1, odd = j & 1;
        const int rA[2] = {448 * i2 + 320 * odd, 448 * i2 + 320 - 320 * odd}, rB[2] = {448 * i2 + 128 + 96 * odd, 448 * i2 + 224 - 96 * odd};
        int pos = 0, ph = 0;
        for (int i = 0; i < 64; i++) {
            uint32_t wb = 0, par = 0, fb = 0, dst = 0, small = 0, map = 0, c0 = 0, c2 = 0, c4 = 0;
            if (i >= 8 && i < 12) {
                wb = B_XFREE; fb = B_QFULL + (i - 8) * 8; dst = SM_A + (i - 8) * 16384 + rank * 8192; c0 = j * 64; c2 = (i - 8) * 128 + rank * 64;
            } else {
                const int n = i < 8 ? i : i - 4;
                if (n < 8) { c0 = 512 + rank * 512 + j * 64; c2 = n * 64; }
                else if (n < 12) { map = 1; c0 = j * 64; c4 = piece_of((n - 8) * 2 + rank, j); }
                else if (n < 28) { map = 2 + rank; c2 = piece_of((n - 12) >> 1, j) * 8 + (n & 1) * 4; c4 = 7 * i2 + 5 * odd; }
                else if (n < 44) { map = 4 + rank; small = 1; c2 = piece_of((n - 28) >> 1, j) * 8 + (n & 1) * 4; c4 = 14 * i2 + 4 + 3 * odd; }
                else if (n < 52) { small = n >= 48; map = 6 + small; c0 = ((j + 2 + 2 * rank) & 7) * 64; c2 = small ? rB[(n >> 1) & 1] + (n & 1) * 48 : rA[(n >> 1) & 1] + (n & 1) * 64; }
                else { small = n & 1; map = 6 + small; c0 = ((j + (n < 56 ? 6 : 0)) & 7) * 64; c2 = small ? rB[(n >> 1) & 1] + rank * 48 : rA[(n >> 1) & 1] + rank * 64; }
                wb = n == 12 ? B_MFREE : B_EMPTY + pos * 8; par = n == 12 ? 0 : ph ^ 1;
                fb = B_FULL + pos * 8; dst = SM_RING + pos * 16384 + rank * (small ? 6144 : 8192);
                if (++pos == NST) { pos = 0; ph ^= 1; }
                if (n < 8 && pos == 3) pos = n < 7 ? 4 : 5;
            }
            t.e[jr][i].x = (wb - SM_BAR) | par << 9 | (fb - SM_BAR) << 10 | small << 19 | map << 20 | (dst >> 11) << 24;
            t.e[jr][i].y = c0 | c2 << 11 | c4 << 22;
        }
    }
    return t;
}
__device__ const Sched g_sched = make_sched();

__device__ __forceinline__ void mbar_init(uint32_t bar, uint32_t cnt) { asm volatile("mbarrier.init.shared::cta.b64 [%0], %1;" :: "r"(bar), "r"(cnt) : "memory"); }
__device__ __forceinline__ void mbar_expect(uint32_t bar, uint32_t bytes) { asm volatile("mbarrier.arrive.expect_tx.shared::cta.b64 _, [%0], %1;" :: "r"(bar), "r"(bytes) : "memory"); }
__device__ __forceinline__ void mbar_arrive(uint32_t bar) { asm volatile("mbarrier.arrive.shared::cta.b64 _, [%0];" :: "r"(bar) : "memory"); }
__device__ __forceinline__ void mbar_arrive_cl(uint32_t cluster_addr) { asm volatile("mbarrier.arrive.shared::cluster.b64 _, [%0];" :: "r"(cluster_addr) : "memory"); }
__device__ __forceinline__ uint32_t mapa(uint32_t addr, uint32_t cta) { uint32_t r; asm("mapa.shared::cluster.u32 %0, %1, %2;" : "=r"(r) : "r"(addr), "r"(cta)); return r; }
constexpr int SPIN_LIMIT = 1 << 17;
__device__ __forceinline__ void mbar_wait(uint32_t bar, uint32_t parity) {
    asm volatile("{ .reg .pred p;\n"
                 "W: mbarrier.try_wait.parity.shared::cta.b64 p, [%0], %1;\n"
                 "@!p bra W; }" :: "r"(bar), "r"(parity) : "memory");
}
__device__ __forceinline__ void mbar_waitc(uint32_t bar, uint32_t parity) {
    asm volatile("{ .reg .pred p; .reg .u32 n; mov.u32 n, 0;\n"
                 "W: mbarrier.try_wait.parity.shared::cta.b64 p, [%0], %1;\n"
                 "add.u32 n, n, 1; setp.lt.and.u32 p, n, 0x7fffffff, !p;\n"
                 "@p bra W; }" :: "r"(bar), "r"(parity) : "memory");
}
__device__ __forceinline__ void mbar_watch(uint32_t bar, uint32_t parity = 0) {
    asm volatile("{ .reg .pred p; .reg .u32 n; mov.u32 n, 0;\n"
                 "W: mbarrier.try_wait.parity.shared::cta.b64 p, [%0], %2, 2000;\n"
                 "@p bra D;\n"
                 "add.u32 n, n, 1; setp.lt.u32 p, n, %1;\n"
                 "@p bra W;\n"
                 "trap;\n"
                 "D: }" :: "r"(bar), "n"(SPIN_LIMIT), "r"(parity) : "memory");
}
__device__ __forceinline__ bool elect() { uint32_t p; asm volatile("{ .reg .pred P; elect.sync _|P, 0xffffffff; selp.u32 %0, 1, 0, P; }" : "=r"(p)); return p; }
__device__ __forceinline__ void bar_sync(int id, int n) { asm volatile("bar.sync %0, %1;" :: "r"(id), "r"(n) : "memory"); }
__device__ __forceinline__ void bar_arrive(int id, int n) { asm volatile("bar.arrive %0, %1;" :: "r"(id), "r"(n) : "memory"); }
__device__ __forceinline__ void tma3d(uint32_t dst, const CUtensorMap* m, int c0, int c1, int c2, uint32_t bar) {
    asm volatile("cp.async.bulk.tensor.3d.shared::cluster.global.mbarrier::complete_tx::bytes [%0], [%1, {%3, %4, %5}], [%2];"
        :: "r"(dst), "l"(m), "r"(bar), "r"(c0), "r"(c1), "r"(c2) : "memory");
}
__device__ __forceinline__ void tma2d(uint32_t dst, const CUtensorMap* m, int c0, int c1, uint32_t bar) {
    asm volatile("cp.async.bulk.tensor.2d.shared::cluster.global.mbarrier::complete_tx::bytes [%0], [%1, {%3, %4}], [%2];"
        :: "r"(dst), "l"(m), "r"(bar), "r"(c0), "r"(c1) : "memory");
}
__device__ __forceinline__ void tma5d_mc(uint32_t dst, const CUtensorMap* m, int c0, int c2, int c4, uint32_t bar) {
    asm volatile("cp.async.bulk.tensor.5d.shared::cluster.global.mbarrier::complete_tx::bytes.multicast::cluster [%0], [%1, {%3, %6, %4, %6, %5}], [%2], %7;"
        :: "r"(dst), "l"(m), "r"(bar), "r"(c0), "r"(c2), "r"(c4), "r"(0), "h"((uint16_t)3) : "memory");
}
__device__ __forceinline__ void bulk_load(uint32_t dst, const void* src, uint32_t bytes, uint32_t bar) {
    asm volatile("cp.async.bulk.shared::cluster.global.mbarrier::complete_tx::bytes [%0], [%1], %2, [%3];" :: "r"(dst), "l"(src), "r"(bytes), "r"(bar) : "memory");
}
__device__ __forceinline__ void l2_prefetch(const void* src, uint32_t bytes) { asm volatile("cp.async.bulk.prefetch.L2.global [%0], %1;" :: "l"(src), "r"(bytes) : "memory"); }
__device__ __forceinline__ void tmap_prefetch(const CUtensorMap* m) { asm volatile("prefetch.tensormap [%0];" :: "l"(m) : "memory"); }
__device__ __forceinline__ void fence_async_smem() { asm volatile("fence.proxy.async.shared::cta;" ::: "memory"); }
__device__ __forceinline__ uint32_t ld_rlx(const void* p) { uint32_t v; asm volatile("ld.relaxed.gpu.global.u32 %0, [%1];" : "=r"(v) : "l"(p) : "memory"); return v; }
__device__ __forceinline__ uint4 ld_rlx4(const void* p) { uint4 v; asm volatile("ld.relaxed.gpu.global.v4.u32 {%0,%1,%2,%3}, [%4];" : "=r"(v.x), "=r"(v.y), "=r"(v.z), "=r"(v.w) : "l"(p) : "memory"); return v; }
__device__ __forceinline__ void st_rlx(void* p, uint32_t v) { asm volatile("st.relaxed.gpu.global.u32 [%0], %1;" :: "l"(p), "r"(v) : "memory"); }
__device__ __forceinline__ uint32_t ldg_nc(const void* p) { uint32_t v; asm volatile("ld.global.nc.u32 %0, [%1];" : "=r"(v) : "l"(p)); return v; }
__device__ __forceinline__ uint2 ldg_nc2(const void* p) { uint2 v; asm volatile("ld.global.nc.v2.u32 {%0,%1}, [%2];" : "=r"(v.x), "=r"(v.y) : "l"(p)); return v; }
__device__ __forceinline__ void stg4(void* p, const uint32_t* v) { asm volatile("st.global.v4.u32 [%0], {%1,%2,%3,%4};" :: "l"(p), "r"(v[0]), "r"(v[1]), "r"(v[2]), "r"(v[3]) : "memory"); }
__device__ __forceinline__ void lds4(uint32_t* v, uint32_t a) { asm volatile("ld.shared.v4.u32 {%0,%1,%2,%3}, [%4];" : "=r"(v[0]), "=r"(v[1]), "=r"(v[2]), "=r"(v[3]) : "r"(a) : "memory"); }
__device__ __forceinline__ void lds2f(float* v, uint32_t a) { asm volatile("ld.shared.v2.f32 {%0,%1}, [%2];" : "=f"(v[0]), "=f"(v[1]) : "r"(a) : "memory"); }
__device__ __forceinline__ float lds1f(uint32_t a) { float v; asm volatile("ld.shared.f32 %0, [%1];" : "=f"(v) : "r"(a) : "memory"); return v; }
__device__ __forceinline__ void sts4(uint32_t a, const uint32_t* v) { asm volatile("st.shared.v4.u32 [%0], {%1,%2,%3,%4};" :: "r"(a), "r"(v[0]), "r"(v[1]), "r"(v[2]), "r"(v[3]) : "memory"); }
__device__ __forceinline__ void sts2(uint32_t a, uint32_t x, uint32_t y) { asm volatile("st.shared.v2.u32 [%0], {%1,%2};" :: "r"(a), "r"(x), "r"(y) : "memory"); }
__device__ __forceinline__ void sts1(uint32_t a, uint32_t v) { asm volatile("st.shared.u32 [%0], %1;" :: "r"(a), "r"(v) : "memory"); }
__device__ __forceinline__ void ldsm4(uint32_t* v, uint32_t a) { asm volatile("ldmatrix.sync.aligned.m8n8.x4.shared.b16 {%0,%1,%2,%3}, [%4];" : "=r"(v[0]), "=r"(v[1]), "=r"(v[2]), "=r"(v[3]) : "r"(a) : "memory"); }
__device__ __forceinline__ void stsm4(uint32_t a, const uint32_t* v) { asm volatile("stmatrix.sync.aligned.m8n8.x4.shared.b16 [%0], {%1,%2,%3,%4};" :: "r"(a), "r"(v[0]), "r"(v[1]), "r"(v[2]), "r"(v[3]) : "memory"); }
__device__ __forceinline__ void mma16816(float* c, uint32_t a0, uint32_t a1, uint32_t a2, uint32_t a3, uint32_t b0, uint32_t b1) {
    asm volatile("mma.sync.aligned.m16n8k16.row.col.f32.bf16.bf16.f32 {%0,%1,%2,%3}, {%4,%5,%6,%7}, {%8,%9}, {%0,%1,%2,%3};"
        : "+f"(c[0]), "+f"(c[1]), "+f"(c[2]), "+f"(c[3]) : "r"(a0), "r"(a1), "r"(a2), "r"(a3), "r"(b0), "r"(b1));
}
__device__ __forceinline__ uint32_t pack2(float lo, float hi) { uint32_t r; asm("cvt.rn.bf16x2.f32 %0, %1, %2;" : "=r"(r) : "f"(hi), "f"(lo)); return r; }
__device__ __forceinline__ uint32_t reglu2(float g0, float g1, float u0, float u1) {
    uint32_t r;
    asm("{ .reg .b32 g, u; cvt.rn.relu.bf16x2.f32 g, %2, %1; cvt.rn.bf16x2.f32 u, %4, %3; mul.rn.bf16x2 %0, g, u; }" : "=r"(r) : "f"(g0), "f"(g1), "f"(u0), "f"(u1));
    return r;
}
__device__ __forceinline__ float bf_lo(uint32_t v) { return __uint_as_float(v << 16); }
__device__ __forceinline__ float bf_hi(uint32_t v) { return __uint_as_float(v & 0xFFFF0000u); }
__device__ __forceinline__ float bf_round(float x) { return bf_lo(pack2(x, 0.f)); }
__device__ __forceinline__ uint32_t hfma2(uint32_t a, uint32_t b, uint32_t c) { uint32_t r; asm("fma.rn.bf16x2 %0, %1, %2, %3;" : "=r"(r) : "r"(a), "r"(b), "r"(c)); return r; }
__device__ __forceinline__ uint32_t hadd2(uint32_t a, uint32_t b) { uint32_t r; asm("add.rn.bf16x2 %0, %1, %2;" : "=r"(r) : "r"(a), "r"(b)); return r; }
__device__ __forceinline__ float ex2(float x) { float r; asm("ex2.approx.ftz.f32 %0, %1;" : "=f"(r) : "f"(x)); return r; }
__device__ __forceinline__ float rcp(float x) { float r; asm("rcp.approx.ftz.f32 %0, %1;" : "=f"(r) : "f"(x)); return r; }
__device__ __forceinline__ float rsq(float x) { float r; asm("rsqrt.approx.ftz.f32 %0, %1;" : "=f"(r) : "f"(x)); return r; }
__device__ __forceinline__ float silu_bf(uint32_t bits) { float c = __uint_as_float(bits << 16); return bf_round(c * rcp(1.f + ex2(-1.4426950408889634f * c))); }
__device__ __forceinline__ void wg_fence() { asm volatile("wgmma.fence.sync.aligned;" ::: "memory"); }
__device__ __forceinline__ void wg_commit() { asm volatile("wgmma.commit_group.sync.aligned;" ::: "memory"); }
template <int N> __device__ __forceinline__ void wg_wait() { asm volatile("wgmma.wait_group.sync.aligned %0;" :: "n"(N) : "memory"); }
template <int N> __device__ __forceinline__ void pin(float* d) {
#pragma unroll
    for (int i = 0; i < N; i++) asm volatile("" : "+f"(d[i]) :: "memory");
}
template <int N> __device__ __forceinline__ void pin(uint32_t* d) {
#pragma unroll
    for (int i = 0; i < N; i++) asm volatile("" : "+r"(d[i]) :: "memory");
}
__device__ __forceinline__ uint64_t desc(uint32_t d0, uint32_t off, uint32_t lbo = 0, uint32_t hi = 0x40000040u) {
    return (uint64_t)(d0 + (off >> 4) + ((lbo >> 4) << 16)) | ((uint64_t)hi << 32);
}
__device__ __forceinline__ void sts_word(uint32_t a, uint32_t v, int h) {
    const uint32_t w[4] = {h == 0 ? v : 0u, h == 1 ? v : 0u, h == 2 ? v : 0u, h == 3 ? v : 0u};
    sts4(a, w);
}

__device__ __forceinline__ void wg_rs72(float* d, const uint32_t* a, uint64_t db) {
    asm volatile("{ .reg .pred p; setp.ne.b32 p, %41, 0;\n"
        "wgmma.mma_async.sync.aligned.m64n72k16.f32.bf16.bf16 {"
        "%0, %1, %2, %3, %4, %5, %6, %7, %8, %9, %10, %11, %12, %13, %14, %15, "
        "%16, %17, %18, %19, %20, %21, %22, %23, %24, %25, %26, %27, %28, %29, %30, %31, "
        "%32, %33, %34, %35"
        "}, {%36, %37, %38, %39}, %40, p, 1, 1, 1; }"
        : "+f"(d[0]), "+f"(d[1]), "+f"(d[2]), "+f"(d[3]), "+f"(d[4]), "+f"(d[5]), "+f"(d[6]), "+f"(d[7]),
          "+f"(d[8]), "+f"(d[9]), "+f"(d[10]), "+f"(d[11]), "+f"(d[12]), "+f"(d[13]), "+f"(d[14]), "+f"(d[15]),
          "+f"(d[16]), "+f"(d[17]), "+f"(d[18]), "+f"(d[19]), "+f"(d[20]), "+f"(d[21]), "+f"(d[22]), "+f"(d[23]),
          "+f"(d[24]), "+f"(d[25]), "+f"(d[26]), "+f"(d[27]), "+f"(d[28]), "+f"(d[29]), "+f"(d[30]), "+f"(d[31]),
          "+f"(d[32]), "+f"(d[33]), "+f"(d[34]), "+f"(d[35])
        : "r"(a[0]), "r"(a[1]), "r"(a[2]), "r"(a[3]), "l"(db), "n"(1));
}
__device__ __forceinline__ void wg_rs72z(float* d, const uint32_t* a, uint64_t db) {
    asm volatile("{ .reg .pred p; setp.ne.b32 p, %41, 0;\n"
        "wgmma.mma_async.sync.aligned.m64n72k16.f32.bf16.bf16 {"
        "%0, %1, %2, %3, %4, %5, %6, %7, %8, %9, %10, %11, %12, %13, %14, %15, "
        "%16, %17, %18, %19, %20, %21, %22, %23, %24, %25, %26, %27, %28, %29, %30, %31, "
        "%32, %33, %34, %35"
        "}, {%36, %37, %38, %39}, %40, p, 1, 1, 1; }"
        : "=f"(d[0]), "=f"(d[1]), "=f"(d[2]), "=f"(d[3]), "=f"(d[4]), "=f"(d[5]), "=f"(d[6]), "=f"(d[7]),
          "=f"(d[8]), "=f"(d[9]), "=f"(d[10]), "=f"(d[11]), "=f"(d[12]), "=f"(d[13]), "=f"(d[14]), "=f"(d[15]),
          "=f"(d[16]), "=f"(d[17]), "=f"(d[18]), "=f"(d[19]), "=f"(d[20]), "=f"(d[21]), "=f"(d[22]), "=f"(d[23]),
          "=f"(d[24]), "=f"(d[25]), "=f"(d[26]), "=f"(d[27]), "=f"(d[28]), "=f"(d[29]), "=f"(d[30]), "=f"(d[31]),
          "=f"(d[32]), "=f"(d[33]), "=f"(d[34]), "=f"(d[35])
        : "r"(a[0]), "r"(a[1]), "r"(a[2]), "r"(a[3]), "l"(db), "n"(0));
}
__device__ __forceinline__ void wg_rs64(float* d, const uint32_t* a, uint64_t db) {
    asm volatile("{ .reg .pred p; setp.ne.b32 p, %37, 0;\n"
        "wgmma.mma_async.sync.aligned.m64n64k16.f32.bf16.bf16 {"
        "%0, %1, %2, %3, %4, %5, %6, %7, %8, %9, %10, %11, %12, %13, %14, %15, "
        "%16, %17, %18, %19, %20, %21, %22, %23, %24, %25, %26, %27, %28, %29, %30, %31"
        "}, {%32, %33, %34, %35}, %36, p, 1, 1, 1; }"
        : "+f"(d[0]), "+f"(d[1]), "+f"(d[2]), "+f"(d[3]), "+f"(d[4]), "+f"(d[5]), "+f"(d[6]), "+f"(d[7]),
          "+f"(d[8]), "+f"(d[9]), "+f"(d[10]), "+f"(d[11]), "+f"(d[12]), "+f"(d[13]), "+f"(d[14]), "+f"(d[15]),
          "+f"(d[16]), "+f"(d[17]), "+f"(d[18]), "+f"(d[19]), "+f"(d[20]), "+f"(d[21]), "+f"(d[22]), "+f"(d[23]),
          "+f"(d[24]), "+f"(d[25]), "+f"(d[26]), "+f"(d[27]), "+f"(d[28]), "+f"(d[29]), "+f"(d[30]), "+f"(d[31])
        : "r"(a[0]), "r"(a[1]), "r"(a[2]), "r"(a[3]), "l"(db), "n"(1));
}
__device__ __forceinline__ void wg_rs64z(float* d, const uint32_t* a, uint64_t db) {
    asm volatile("{ .reg .pred p; setp.ne.b32 p, %37, 0;\n"
        "wgmma.mma_async.sync.aligned.m64n64k16.f32.bf16.bf16 {"
        "%0, %1, %2, %3, %4, %5, %6, %7, %8, %9, %10, %11, %12, %13, %14, %15, "
        "%16, %17, %18, %19, %20, %21, %22, %23, %24, %25, %26, %27, %28, %29, %30, %31"
        "}, {%32, %33, %34, %35}, %36, p, 1, 1, 1; }"
        : "=f"(d[0]), "=f"(d[1]), "=f"(d[2]), "=f"(d[3]), "=f"(d[4]), "=f"(d[5]), "=f"(d[6]), "=f"(d[7]),
          "=f"(d[8]), "=f"(d[9]), "=f"(d[10]), "=f"(d[11]), "=f"(d[12]), "=f"(d[13]), "=f"(d[14]), "=f"(d[15]),
          "=f"(d[16]), "=f"(d[17]), "=f"(d[18]), "=f"(d[19]), "=f"(d[20]), "=f"(d[21]), "=f"(d[22]), "=f"(d[23]),
          "=f"(d[24]), "=f"(d[25]), "=f"(d[26]), "=f"(d[27]), "=f"(d[28]), "=f"(d[29]), "=f"(d[30]), "=f"(d[31])
        : "r"(a[0]), "r"(a[1]), "r"(a[2]), "r"(a[3]), "l"(db), "n"(0));
}
__device__ __forceinline__ void wg_rs128(float* d, const uint32_t* a, uint64_t db) {
    asm volatile("{ .reg .pred p; setp.ne.b32 p, %69, 0;\n"
        "wgmma.mma_async.sync.aligned.m64n128k16.f32.bf16.bf16 {"
        "%0, %1, %2, %3, %4, %5, %6, %7, %8, %9, %10, %11, %12, %13, %14, %15, "
        "%16, %17, %18, %19, %20, %21, %22, %23, %24, %25, %26, %27, %28, %29, %30, %31, "
        "%32, %33, %34, %35, %36, %37, %38, %39, %40, %41, %42, %43, %44, %45, %46, %47, "
        "%48, %49, %50, %51, %52, %53, %54, %55, %56, %57, %58, %59, %60, %61, %62, %63"
        "}, {%64, %65, %66, %67}, %68, p, 1, 1, 1; }"
        : "+f"(d[0]), "+f"(d[1]), "+f"(d[2]), "+f"(d[3]), "+f"(d[4]), "+f"(d[5]), "+f"(d[6]), "+f"(d[7]),
          "+f"(d[8]), "+f"(d[9]), "+f"(d[10]), "+f"(d[11]), "+f"(d[12]), "+f"(d[13]), "+f"(d[14]), "+f"(d[15]),
          "+f"(d[16]), "+f"(d[17]), "+f"(d[18]), "+f"(d[19]), "+f"(d[20]), "+f"(d[21]), "+f"(d[22]), "+f"(d[23]),
          "+f"(d[24]), "+f"(d[25]), "+f"(d[26]), "+f"(d[27]), "+f"(d[28]), "+f"(d[29]), "+f"(d[30]), "+f"(d[31]),
          "+f"(d[32]), "+f"(d[33]), "+f"(d[34]), "+f"(d[35]), "+f"(d[36]), "+f"(d[37]), "+f"(d[38]), "+f"(d[39]),
          "+f"(d[40]), "+f"(d[41]), "+f"(d[42]), "+f"(d[43]), "+f"(d[44]), "+f"(d[45]), "+f"(d[46]), "+f"(d[47]),
          "+f"(d[48]), "+f"(d[49]), "+f"(d[50]), "+f"(d[51]), "+f"(d[52]), "+f"(d[53]), "+f"(d[54]), "+f"(d[55]),
          "+f"(d[56]), "+f"(d[57]), "+f"(d[58]), "+f"(d[59]), "+f"(d[60]), "+f"(d[61]), "+f"(d[62]), "+f"(d[63])
        : "r"(a[0]), "r"(a[1]), "r"(a[2]), "r"(a[3]), "l"(db), "n"(1));
}
__device__ __forceinline__ void wg_rs128z(float* d, const uint32_t* a, uint64_t db) {
    asm volatile("{ .reg .pred p; setp.ne.b32 p, %69, 0;\n"
        "wgmma.mma_async.sync.aligned.m64n128k16.f32.bf16.bf16 {"
        "%0, %1, %2, %3, %4, %5, %6, %7, %8, %9, %10, %11, %12, %13, %14, %15, "
        "%16, %17, %18, %19, %20, %21, %22, %23, %24, %25, %26, %27, %28, %29, %30, %31, "
        "%32, %33, %34, %35, %36, %37, %38, %39, %40, %41, %42, %43, %44, %45, %46, %47, "
        "%48, %49, %50, %51, %52, %53, %54, %55, %56, %57, %58, %59, %60, %61, %62, %63"
        "}, {%64, %65, %66, %67}, %68, p, 1, 1, 1; }"
        : "=f"(d[0]), "=f"(d[1]), "=f"(d[2]), "=f"(d[3]), "=f"(d[4]), "=f"(d[5]), "=f"(d[6]), "=f"(d[7]),
          "=f"(d[8]), "=f"(d[9]), "=f"(d[10]), "=f"(d[11]), "=f"(d[12]), "=f"(d[13]), "=f"(d[14]), "=f"(d[15]),
          "=f"(d[16]), "=f"(d[17]), "=f"(d[18]), "=f"(d[19]), "=f"(d[20]), "=f"(d[21]), "=f"(d[22]), "=f"(d[23]),
          "=f"(d[24]), "=f"(d[25]), "=f"(d[26]), "=f"(d[27]), "=f"(d[28]), "=f"(d[29]), "=f"(d[30]), "=f"(d[31]),
          "=f"(d[32]), "=f"(d[33]), "=f"(d[34]), "=f"(d[35]), "=f"(d[36]), "=f"(d[37]), "=f"(d[38]), "=f"(d[39]),
          "=f"(d[40]), "=f"(d[41]), "=f"(d[42]), "=f"(d[43]), "=f"(d[44]), "=f"(d[45]), "=f"(d[46]), "=f"(d[47]),
          "=f"(d[48]), "=f"(d[49]), "=f"(d[50]), "=f"(d[51]), "=f"(d[52]), "=f"(d[53]), "=f"(d[54]), "=f"(d[55]),
          "=f"(d[56]), "=f"(d[57]), "=f"(d[58]), "=f"(d[59]), "=f"(d[60]), "=f"(d[61]), "=f"(d[62]), "=f"(d[63])
        : "r"(a[0]), "r"(a[1]), "r"(a[2]), "r"(a[3]), "l"(db), "n"(0));
}
__device__ __forceinline__ void wg_ss64(float* d, uint64_t da, uint64_t db) {
    asm volatile("{ .reg .pred p; setp.ne.b32 p, %34, 0;\n"
        "wgmma.mma_async.sync.aligned.m64n64k16.f32.bf16.bf16 {"
        "%0, %1, %2, %3, %4, %5, %6, %7, %8, %9, %10, %11, %12, %13, %14, %15, "
        "%16, %17, %18, %19, %20, %21, %22, %23, %24, %25, %26, %27, %28, %29, %30, %31"
        "}, %32, %33, p, 1, 1, 0, 1; }"
        : "+f"(d[0]), "+f"(d[1]), "+f"(d[2]), "+f"(d[3]), "+f"(d[4]), "+f"(d[5]), "+f"(d[6]), "+f"(d[7]),
          "+f"(d[8]), "+f"(d[9]), "+f"(d[10]), "+f"(d[11]), "+f"(d[12]), "+f"(d[13]), "+f"(d[14]), "+f"(d[15]),
          "+f"(d[16]), "+f"(d[17]), "+f"(d[18]), "+f"(d[19]), "+f"(d[20]), "+f"(d[21]), "+f"(d[22]), "+f"(d[23]),
          "+f"(d[24]), "+f"(d[25]), "+f"(d[26]), "+f"(d[27]), "+f"(d[28]), "+f"(d[29]), "+f"(d[30]), "+f"(d[31])
        : "l"(da), "l"(db), "n"(1));
}
__device__ __forceinline__ void wg_ss64z(float* d, uint64_t da, uint64_t db) {
    asm volatile("{ .reg .pred p; setp.ne.b32 p, %34, 0;\n"
        "wgmma.mma_async.sync.aligned.m64n64k16.f32.bf16.bf16 {"
        "%0, %1, %2, %3, %4, %5, %6, %7, %8, %9, %10, %11, %12, %13, %14, %15, "
        "%16, %17, %18, %19, %20, %21, %22, %23, %24, %25, %26, %27, %28, %29, %30, %31"
        "}, %32, %33, p, 1, 1, 0, 1; }"
        : "=f"(d[0]), "=f"(d[1]), "=f"(d[2]), "=f"(d[3]), "=f"(d[4]), "=f"(d[5]), "=f"(d[6]), "=f"(d[7]),
          "=f"(d[8]), "=f"(d[9]), "=f"(d[10]), "=f"(d[11]), "=f"(d[12]), "=f"(d[13]), "=f"(d[14]), "=f"(d[15]),
          "=f"(d[16]), "=f"(d[17]), "=f"(d[18]), "=f"(d[19]), "=f"(d[20]), "=f"(d[21]), "=f"(d[22]), "=f"(d[23]),
          "=f"(d[24]), "=f"(d[25]), "=f"(d[26]), "=f"(d[27]), "=f"(d[28]), "=f"(d[29]), "=f"(d[30]), "=f"(d[31])
        : "l"(da), "l"(db), "n"(0));
}
__device__ __forceinline__ void wg_ss192(float* d, uint64_t da, uint64_t db, int sc) {
    asm volatile("{ .reg .pred p; setp.ne.b32 p, %98, 0;\n"
        "wgmma.mma_async.sync.aligned.m64n192k16.f32.bf16.bf16 {"
        "%0, %1, %2, %3, %4, %5, %6, %7, %8, %9, %10, %11, %12, %13, %14, %15, "
        "%16, %17, %18, %19, %20, %21, %22, %23, %24, %25, %26, %27, %28, %29, %30, %31, "
        "%32, %33, %34, %35, %36, %37, %38, %39, %40, %41, %42, %43, %44, %45, %46, %47, "
        "%48, %49, %50, %51, %52, %53, %54, %55, %56, %57, %58, %59, %60, %61, %62, %63, "
        "%64, %65, %66, %67, %68, %69, %70, %71, %72, %73, %74, %75, %76, %77, %78, %79, "
        "%80, %81, %82, %83, %84, %85, %86, %87, %88, %89, %90, %91, %92, %93, %94, %95"
        "}, %96, %97, p, 1, 1, 0, 1; }"
        : "+f"(d[0]), "+f"(d[1]), "+f"(d[2]), "+f"(d[3]), "+f"(d[4]), "+f"(d[5]), "+f"(d[6]), "+f"(d[7]),
          "+f"(d[8]), "+f"(d[9]), "+f"(d[10]), "+f"(d[11]), "+f"(d[12]), "+f"(d[13]), "+f"(d[14]), "+f"(d[15]),
          "+f"(d[16]), "+f"(d[17]), "+f"(d[18]), "+f"(d[19]), "+f"(d[20]), "+f"(d[21]), "+f"(d[22]), "+f"(d[23]),
          "+f"(d[24]), "+f"(d[25]), "+f"(d[26]), "+f"(d[27]), "+f"(d[28]), "+f"(d[29]), "+f"(d[30]), "+f"(d[31]),
          "+f"(d[32]), "+f"(d[33]), "+f"(d[34]), "+f"(d[35]), "+f"(d[36]), "+f"(d[37]), "+f"(d[38]), "+f"(d[39]),
          "+f"(d[40]), "+f"(d[41]), "+f"(d[42]), "+f"(d[43]), "+f"(d[44]), "+f"(d[45]), "+f"(d[46]), "+f"(d[47]),
          "+f"(d[48]), "+f"(d[49]), "+f"(d[50]), "+f"(d[51]), "+f"(d[52]), "+f"(d[53]), "+f"(d[54]), "+f"(d[55]),
          "+f"(d[56]), "+f"(d[57]), "+f"(d[58]), "+f"(d[59]), "+f"(d[60]), "+f"(d[61]), "+f"(d[62]), "+f"(d[63]),
          "+f"(d[64]), "+f"(d[65]), "+f"(d[66]), "+f"(d[67]), "+f"(d[68]), "+f"(d[69]), "+f"(d[70]), "+f"(d[71]),
          "+f"(d[72]), "+f"(d[73]), "+f"(d[74]), "+f"(d[75]), "+f"(d[76]), "+f"(d[77]), "+f"(d[78]), "+f"(d[79]),
          "+f"(d[80]), "+f"(d[81]), "+f"(d[82]), "+f"(d[83]), "+f"(d[84]), "+f"(d[85]), "+f"(d[86]), "+f"(d[87]),
          "+f"(d[88]), "+f"(d[89]), "+f"(d[90]), "+f"(d[91]), "+f"(d[92]), "+f"(d[93]), "+f"(d[94]), "+f"(d[95])
        : "l"(da), "l"(db), "r"(sc));
}
__device__ __forceinline__ void wg_ss256(float* d, uint64_t da, uint64_t db, int sc) {
    asm volatile("{ .reg .pred p; setp.ne.b32 p, %130, 0;\n"
        "wgmma.mma_async.sync.aligned.m64n256k16.f32.bf16.bf16 {"
        "%0, %1, %2, %3, %4, %5, %6, %7, %8, %9, %10, %11, %12, %13, %14, %15, "
        "%16, %17, %18, %19, %20, %21, %22, %23, %24, %25, %26, %27, %28, %29, %30, %31, "
        "%32, %33, %34, %35, %36, %37, %38, %39, %40, %41, %42, %43, %44, %45, %46, %47, "
        "%48, %49, %50, %51, %52, %53, %54, %55, %56, %57, %58, %59, %60, %61, %62, %63, "
        "%64, %65, %66, %67, %68, %69, %70, %71, %72, %73, %74, %75, %76, %77, %78, %79, "
        "%80, %81, %82, %83, %84, %85, %86, %87, %88, %89, %90, %91, %92, %93, %94, %95, "
        "%96, %97, %98, %99, %100, %101, %102, %103, %104, %105, %106, %107, %108, %109, %110, %111, "
        "%112, %113, %114, %115, %116, %117, %118, %119, %120, %121, %122, %123, %124, %125, %126, %127"
        "}, %128, %129, p, 1, 1, 0, 1; }"
        : "+f"(d[0]), "+f"(d[1]), "+f"(d[2]), "+f"(d[3]), "+f"(d[4]), "+f"(d[5]), "+f"(d[6]), "+f"(d[7]),
          "+f"(d[8]), "+f"(d[9]), "+f"(d[10]), "+f"(d[11]), "+f"(d[12]), "+f"(d[13]), "+f"(d[14]), "+f"(d[15]),
          "+f"(d[16]), "+f"(d[17]), "+f"(d[18]), "+f"(d[19]), "+f"(d[20]), "+f"(d[21]), "+f"(d[22]), "+f"(d[23]),
          "+f"(d[24]), "+f"(d[25]), "+f"(d[26]), "+f"(d[27]), "+f"(d[28]), "+f"(d[29]), "+f"(d[30]), "+f"(d[31]),
          "+f"(d[32]), "+f"(d[33]), "+f"(d[34]), "+f"(d[35]), "+f"(d[36]), "+f"(d[37]), "+f"(d[38]), "+f"(d[39]),
          "+f"(d[40]), "+f"(d[41]), "+f"(d[42]), "+f"(d[43]), "+f"(d[44]), "+f"(d[45]), "+f"(d[46]), "+f"(d[47]),
          "+f"(d[48]), "+f"(d[49]), "+f"(d[50]), "+f"(d[51]), "+f"(d[52]), "+f"(d[53]), "+f"(d[54]), "+f"(d[55]),
          "+f"(d[56]), "+f"(d[57]), "+f"(d[58]), "+f"(d[59]), "+f"(d[60]), "+f"(d[61]), "+f"(d[62]), "+f"(d[63]),
          "+f"(d[64]), "+f"(d[65]), "+f"(d[66]), "+f"(d[67]), "+f"(d[68]), "+f"(d[69]), "+f"(d[70]), "+f"(d[71]),
          "+f"(d[72]), "+f"(d[73]), "+f"(d[74]), "+f"(d[75]), "+f"(d[76]), "+f"(d[77]), "+f"(d[78]), "+f"(d[79]),
          "+f"(d[80]), "+f"(d[81]), "+f"(d[82]), "+f"(d[83]), "+f"(d[84]), "+f"(d[85]), "+f"(d[86]), "+f"(d[87]),
          "+f"(d[88]), "+f"(d[89]), "+f"(d[90]), "+f"(d[91]), "+f"(d[92]), "+f"(d[93]), "+f"(d[94]), "+f"(d[95]),
          "+f"(d[96]), "+f"(d[97]), "+f"(d[98]), "+f"(d[99]), "+f"(d[100]), "+f"(d[101]), "+f"(d[102]), "+f"(d[103]),
          "+f"(d[104]), "+f"(d[105]), "+f"(d[106]), "+f"(d[107]), "+f"(d[108]), "+f"(d[109]), "+f"(d[110]), "+f"(d[111]),
          "+f"(d[112]), "+f"(d[113]), "+f"(d[114]), "+f"(d[115]), "+f"(d[116]), "+f"(d[117]), "+f"(d[118]), "+f"(d[119]),
          "+f"(d[120]), "+f"(d[121]), "+f"(d[122]), "+f"(d[123]), "+f"(d[124]), "+f"(d[125]), "+f"(d[126]), "+f"(d[127])
        : "l"(da), "l"(db), "r"(sc));
}
__device__ __forceinline__ void wg_ss40(float* d, uint64_t da, uint64_t db) {
    asm volatile("{ .reg .pred p; setp.ne.b32 p, %22, 0;\n"
        "wgmma.mma_async.sync.aligned.m64n40k16.f32.bf16.bf16 {"
        "%0, %1, %2, %3, %4, %5, %6, %7, %8, %9, %10, %11, %12, %13, %14, %15, "
        "%16, %17, %18, %19"
        "}, %20, %21, p, 1, 1, 1, 1; }"
        : "+f"(d[0]), "+f"(d[1]), "+f"(d[2]), "+f"(d[3]), "+f"(d[4]), "+f"(d[5]), "+f"(d[6]), "+f"(d[7]),
          "+f"(d[8]), "+f"(d[9]), "+f"(d[10]), "+f"(d[11]), "+f"(d[12]), "+f"(d[13]), "+f"(d[14]), "+f"(d[15]),
          "+f"(d[16]), "+f"(d[17]), "+f"(d[18]), "+f"(d[19])
        : "l"(da), "l"(db), "n"(1));
}
__device__ __forceinline__ void wg_ss40z(float* d, uint64_t da, uint64_t db) {
    asm volatile("{ .reg .pred p; setp.ne.b32 p, %22, 0;\n"
        "wgmma.mma_async.sync.aligned.m64n40k16.f32.bf16.bf16 {"
        "%0, %1, %2, %3, %4, %5, %6, %7, %8, %9, %10, %11, %12, %13, %14, %15, "
        "%16, %17, %18, %19"
        "}, %20, %21, p, 1, 1, 1, 1; }"
        : "=f"(d[0]), "=f"(d[1]), "=f"(d[2]), "=f"(d[3]), "=f"(d[4]), "=f"(d[5]), "=f"(d[6]), "=f"(d[7]),
          "=f"(d[8]), "=f"(d[9]), "=f"(d[10]), "=f"(d[11]), "=f"(d[12]), "=f"(d[13]), "=f"(d[14]), "=f"(d[15]),
          "=f"(d[16]), "=f"(d[17]), "=f"(d[18]), "=f"(d[19])
        : "l"(da), "l"(db), "n"(0));
}

__device__ __forceinline__ float quad_tsum(float v0, float v1, float v2, float v3, int q) {
    bool b1 = q & 2, b0 = q & 1;
    float k0 = b1 ? v2 : v0, k1 = b1 ? v3 : v1, s0 = b1 ? v0 : v2, s1 = b1 ? v1 : v3;
    k0 += __shfl_xor_sync(~0u, s0, 2);
    k1 += __shfl_xor_sync(~0u, s1, 2);
    float k = b0 ? k1 : k0, s = b0 ? k0 : k1;
    return k + __shfl_xor_sync(~0u, s, 1);
}

__device__ __forceinline__ float tsum8(float* v, int lane) {
    const bool b4 = lane & 16, b3 = lane & 8, b2 = lane & 4;
#pragma unroll
    for (int i = 0; i < 4; i++) v[i] = (b4 ? v[i + 4] : v[i]) + __shfl_xor_sync(~0u, b4 ? v[i] : v[i + 4], 16);
#pragma unroll
    for (int i = 0; i < 2; i++) v[i] = (b3 ? v[i + 2] : v[i]) + __shfl_xor_sync(~0u, b3 ? v[i] : v[i + 2], 8);
    return (b2 ? v[1] : v[0]) + __shfl_xor_sync(~0u, b2 ? v[0] : v[1], 4);
}

template <bool NORM, int R0 = 0, int R1 = 2>
__device__ __forceinline__ void feature_map(const float* p, uint32_t* f, uint32_t zero) {
    constexpr float L = 1.4426950408889634f;
#pragma unroll
    for (int r = R0; r < R1; r++) {
        float mx = fmaxf(p[2 * r], p[2 * r + 1]), mn = fminf(p[2 * r], p[2 * r + 1]);
#pragma unroll
        for (int t = 1; t < 8; t++) {
            mx = fmaxf(mx, fmaxf(p[4 * t + 2 * r], p[4 * t + 2 * r + 1]));
            mn = fminf(mn, fminf(p[4 * t + 2 * r], p[4 * t + 2 * r + 1]));
        }
#pragma unroll
        for (int sgn = 0; sgn < 2; sgn++) {
            const float sc = sgn ? -L : L;
            float off = sgn ? L * mn : -L * mx;
            if (r == 1) off = __uint_as_float(__float_as_uint(off) | (f[2 * (sgn * 8 + 7)] & zero));
            float e[16];
#pragma unroll
            for (int i = 0; i < 16; i++) e[i] = ex2(fmaf(p[4 * (i >> 1) + 2 * r + (i & 1)], sc, off));
            float inv = 1.f;
            if (NORM) inv = rcp((((e[0] + e[1]) + (e[2] + e[3])) + ((e[4] + e[5]) + (e[6] + e[7]))) + (((e[8] + e[9]) + (e[10] + e[11])) + ((e[12] + e[13]) + (e[14] + e[15]))));
#pragma unroll
            for (int t = 0; t < 8; t++) f[2 * (sgn * 8 + t) + r] = NORM ? pack2(e[2 * t] * inv, e[2 * t + 1] * inv) : pack2(e[2 * t], e[2 * t + 1]);
        }
    }
}

struct Ring {
    uint32_t s = 0, ph = 0;
    __device__ __forceinline__ void next() { if (++s == NST) { s = 0; ph ^= 1; } }
    __device__ __forceinline__ void skip() { next(); if (s == 3) s = 4; }
};

struct Tag { uint32_t tm, tp; };
__device__ __forceinline__ void set_tag(uint32_t* v, Tag t) { asm("lop3.b32 %0, %0, %1, %2, 0xBA;" : "+r"(v[0]) : "r"(t.tm), "r"(t.tp)); }
__device__ __forceinline__ void stg_tagged(void* p, uint32_t* v, Tag t) {
    set_tag(v, t);
    stg4(p, v);
}
template <int N>
__device__ __forceinline__ bool stale(uint32_t (*v)[4], Tag t) {
    uint32_t bad = 0;
#pragma unroll
    for (int k = 0; k < N; k++) bad |= v[k][0] ^ t.tp;
    return __any_sync(~0u, bad & t.tm);
}
template <int N>
__device__ __forceinline__ void ldg_frags(uint32_t (*v)[4], const unsigned char* ga) {
#pragma unroll
    for (int k = 0; k < N; k++) { const uint4 r = ld_rlx4(ga + k * 512); v[k][0] = r.x; v[k][1] = r.y; v[k][2] = r.z; v[k][3] = r.w; }
}
template <int N>
__device__ __forceinline__ void ldg_recheck(uint32_t (*v)[4], const unsigned char* ga, Tag t) {
#pragma unroll 1
    while (__builtin_expect(stale<N>(v, t), 0)) { ldg_frags<N>(v, ga); }
}

template <int N>
__device__ __forceinline__ void lds_checked(uint32_t (*v)[4], uint32_t sa, const unsigned char* ga, Tag t) {
#pragma unroll
    for (int k = 0; k < N; k++) lds4(v[k], sa + k * 512);
    ldg_recheck<N>(v, ga, t);
}

__device__ __forceinline__ void tile_tag(uint32_t (*v)[4], Tag t) {
#pragma unroll
    for (int c = 0; c < 4; c++) set_tag(&v[c][c], t);
}

template <int NT>
__device__ __forceinline__ void tiles_ready(uint32_t bar, uint32_t phase, int i0, uint32_t sa, const unsigned char* ga, int j, int lane, uint32_t par) {
    const uint32_t ca = sa + i0 * 8192 + ((lane >> 2) & 1) * 144 + (lane & 8) * 64 + (lane >> 4) * 1028 + (lane & 3) * 32 + (((lane >> 1) ^ (lane >> 3)) & 1) * 8;
    uint32_t bad = 0;
#pragma unroll
    for (int i = 0; i < NT; i++) {
        mbar_wait(bar + (i0 + i) * 8, phase);
        asm("{ .reg .b32 t; lop3.b32 t, %1, %2, %3, 0x7E; or.b32 %0, %0, t; }" : "+r"(bad) : "r"(__float_as_uint(lds1f(ca + i * 8192))), "r"(__float_as_uint(lds1f(ca + i * 8192 + 256))), "r"(par));
    }
    if (__builtin_expect(__any_sync(~0u, bad & 1), 0)) {
#pragma unroll 1
        for (int k = i0 * 4; k < (i0 + NT) * 4;) {
            const uint4 r = ld_rlx4(ga + piece_of(k >> 2, j) * 8192 + (k & 3) * 512 + lane * 16);
            const uint32_t w[4] = {r.x, r.y, r.z, r.w};
            sts4(sa + (k >> 2) * 8192 + (k & 3) * 512 + lane * 16, w);
            const uint32_t t = ((lane >> 2) ^ k) & 1 ? (k & 2 ? r.w : r.z) : (k & 2 ? r.y : r.x);
            k += !__any_sync(~0u, (t ^ par) & ~(lane ^ (lane >> 3)) & 1);
        }
        fence_async_smem();
        __syncwarp();
    }
}

template <int N>
__device__ __forceinline__ void ffn1_pass(float* acc, uint32_t sb, Ring& rg, uint32_t rel, const unsigned char* gsrc, uint32_t (*pre)[4], uint32_t (*snd)[4], unsigned char* gdst, uint32_t par, int wg, int w4, int j, int lane) {
    uint32_t prev = 0;
    constexpr uint32_t d0 = SM_BASE >> 4;
#pragma unroll 1
    for (int i = 0; i < 8; i++) {
        if (N == 256 && i == 1) { wg_wait<0>(); if (lane < 2) mbar_arrive_cl(rel + prev * 8); }
        if (N == 256 && i > 0) tiles_ready<1>(sb + B_LAND + wg * 64, 1, i, sb + SM_A + wg * 65536 + w4 * 2048, gsrc + w4 * 2048, j, lane, par);
        const uint64_t da = desc(d0, SM_A + wg * 65536 + i * 8192);
#pragma unroll
        for (int h = 0; h < 2; h++) {
            mbar_wait(sb + B_FULL + rg.s * 8, rg.ph);
            const uint32_t st = SM_RING + rg.s * 16384;
            wg_fence();
            if (N == 256) { const uint64_t d = desc(d0, st, 4096); wg_ss256(acc, da + h * 4, d, i + h); wg_ss256(acc, da + h * 4 + 2, d + 128, 1); }
            else          { const uint64_t d = desc(d0, st, 2048, 0x80000020u);  wg_ss192(acc, da + h * 4, d, i + h); wg_ss192(acc, da + h * 4 + 2, d + 64, 1); }
            wg_commit();
            if (N == 192) {
#pragma unroll
                for (int k = 0; k < 8; k++) { const int at = 1 + k * 3 / 2; if (h == (at & 1) && i == (at >> 1)) stg4(gdst + k * 512, snd[k]); }
            }
            wg_wait<1>();
            if ((h || i > (N == 256)) && lane < 2) mbar_arrive_cl(rel + prev * 8);
            prev = rg.s;
            rg.next();
        }
    }
    if (N == 192) ldg_frags<8>(pre, gsrc);
    wg_wait<0>();
    pin<N / 2>(acc);
    if (lane < 2) mbar_arrive_cl(rel + prev * 8);
}

__global__ void __cluster_dims__(2, 1, 1) __launch_bounds__(384, 1) fused_block_kernel(
    const __nv_bfloat16* __restrict__ wmod, const __nv_bfloat16* __restrict__ cvec, unsigned char* __restrict__ scr,
    const __nv_bfloat16* __restrict__ wgate, const __nv_bfloat16* __restrict__ wphi, __nv_bfloat16* __restrict__ out,
    const __nv_bfloat16* __restrict__ wqkv, const __nv_bfloat16* __restrict__ wo,
    const __nv_bfloat16* __restrict__ wup, const __nv_bfloat16* __restrict__ wdown, const Sched* __restrict__ sched, const __grid_constant__ Maps maps) {
    extern __shared__ __align__(1024) unsigned char smem_raw[];
    const uint32_t t0 = (uint32_t)clock();
    uint4 w0, w1; uint32_t c0, c1, ep0;
    {
        const uint32_t t = threadIdx.x & 255, mrow = (blockIdx.x & 3) * 128 + (t >> 2);
        const __nv_bfloat16* wp = wmod + (mrow * 3072 + (blockIdx.x >> 2) * 32 + (t & 3) * 8);
        asm volatile("{ .reg .pred p; .reg .b16 a, b; setp.lt.u32 p, %13, 256;\n"
                     "@p ld.relaxed.gpu.global.v4.u32 {%0,%1,%2,%3}, [%11];\n"
                     "@p ld.relaxed.gpu.global.v4.u32 {%4,%5,%6,%7}, [%11 + 393216];\n"
                     "@p ld.relaxed.cta.global.u16 %8, [%12]; @p ld.relaxed.cta.global.u16 %9, [%12 + 128];\n"
                     "setp.ge.u32 p, %13, 352; @p ld.relaxed.gpu.global.u32 %10, [%14]; }"
            : "=r"(w0.x), "=r"(w0.y), "=r"(w0.z), "=r"(w0.w), "=r"(w1.x), "=r"(w1.y), "=r"(w1.z), "=r"(w1.w), "=r"(c0), "=r"(c1), "=r"(ep0)
            : "l"(wp), "l"(cvec + mrow), "r"(threadIdx.x), "l"(scr + G_MOD1 + (blockIdx.x & 3) * 4096 + (blockIdx.x >> 2) * 128 + (t & 31) * 4) : "memory");
    }
    const uint32_t sb = (uint32_t)__cvta_generic_to_shared(smem_raw);
    if ((sb & 0xFFFFFF) != SM_BASE) return;

    const int tid = threadIdx.x, lane = tid & 31, warp = __shfl_sync(~0u, tid >> 5, 0);
    const int b = blockIdx.x, rank = b & 1, cl = b >> 1;
    int grp, mem;
    if (cl < 4) { grp = 2 * PIV + 1; mem = cl; }
    else if (cl < 36) { grp = 2 * ((cl - 4) & 7); mem = (cl - 4) >> 3; }
    else { mem = (cl - 36) / 7; grp = (cl - 36) - 7 * mem; grp = 2 * (grp + (grp >= PIV)) + 1; }
    const int rb = (grp >> 1) * 2 + rank, j = (grp & 1) * 4 + mem;
    unsigned char* const rs = scr + G_RB * (rb + 1);

    if (warp >= 8 && warp < 11 && elect()) {
        const uint32_t ba = sb + SM_BAR + ((warp - 6) % 3) * 144;
#pragma unroll
        for (int i = 0; i < 18; i++) mbar_init(ba + i * 8, warp == 8 ? 16 : 1);
        asm volatile("fence.mbarrier_init.release.cluster;" ::: "memory");
    }
    __syncwarp();
    asm volatile("barrier.cluster.arrive.relaxed.aligned;" ::: "memory");

    if (warp < 8) {
        const int wg = warp >> 2, w4 = warp & 3, g = lane >> 2, q = lane & 3;
        {
            const float s0 = silu_bf(c0), s1 = silu_bf(c1);
            float v[8];
            v[0] = bf_lo(w0.x) * s0 + bf_lo(w1.x) * s1; v[1] = bf_hi(w0.x) * s0 + bf_hi(w1.x) * s1;
            v[2] = bf_lo(w0.y) * s0 + bf_lo(w1.y) * s1; v[3] = bf_hi(w0.y) * s0 + bf_hi(w1.y) * s1;
            v[4] = bf_lo(w0.z) * s0 + bf_lo(w1.z) * s1; v[5] = bf_hi(w0.z) * s0 + bf_hi(w1.z) * s1;
            v[6] = bf_lo(w0.w) * s0 + bf_lo(w1.w) * s1; v[7] = bf_hi(w0.w) * s0 + bf_hi(w1.w) * s1;
            sts1(sb + SM_RED + warp * 128 + ((lane & 3) * 8 + (lane >> 2)) * 4, __float_as_uint(tsum8(v, lane)));
            bar_arrive(1, 288);
        }
        asm volatile("setmaxnreg.inc.sync.aligned.u32 232;");
        asm volatile("barrier.cluster.wait.aligned;" ::: "memory");
        mbar_wait(sb + B_EPO, 0);
        const uint32_t epoch = __float_as_uint(lds1f(sb + SM_EPO)), tag = epoch;
        st_rlx(rs + G_STAT + warp * 1024 + j * 128 + lane * 4, tag ^ 2);
        uint32_t a[32][4];
        uint32_t r2a, r2b, n2a, n2b;
        const uint32_t lrow = lane & 15, lu = lane >> 4, lx = lane & 7;
        {
            float d[4][4];
            uint4 m[4];
#pragma unroll
            for (int i = 0; i < 16; i++) (&d[0][0])[i] = 0.f;
            constexpr uint32_t ONE = 0x3F803F80u;
            const uint32_t xz = sb + SM_A + wg * 65536 + (w4 * 16 + lx + lu * 8) * 128, xu = (lane >> 3) & 1;
#pragma unroll
            for (int ks = 0; ks < 32; ks++) {
                if ((ks & 7) == 0) {
                    mbar_wait(sb + B_X + wg * 8 + ks * 2, 0);
                    if (ks == POLLK) {
#pragma unroll
                        for (int i = 0; i < 4; i++) m[i] = ld_rlx4(scr + G_MOD1 + i * 4096 + tid * 16);
                    }
#pragma unroll
                    for (int k = ks; k < ks + 8; k++) ldsm4(a[k], xz + (k >> 2) * 8192 + ((((k & 3) * 2 + xu) ^ lx) << 4));
                }
                mma16816(d[(ks & 1) * 2], a[ks][0], ONE, a[ks][1], ONE, a[ks][0], a[ks][1]);
                mma16816(d[(ks & 1) * 2 + 1], a[ks][2], ONE, a[ks][3], ONE, a[ks][2], a[ks][3]);
            }
            if (wg == 0 && lane < 4) mbar_arrive_cl(mapa(sb + B_XFREE, lane & 1));
#pragma unroll 1
            while (true) {
                uint32_t bad = 0;
#pragma unroll
                for (int i = 0; i < 4; i++) bad |= (m[i].x ^ tag) | (m[i].y ^ tag) | (m[i].z ^ tag) | (m[i].w ^ tag);
                if (!__any_sync(~0u, bad & 3)) break;
#pragma unroll
                for (int i = 0; i < 4; i++) m[i] = ld_rlx4(scr + G_MOD1 + i * 4096 + tid * 16);
            }
            const float f0 = (__uint_as_float(m[0].x) + __uint_as_float(m[1].x)) + (__uint_as_float(m[2].x) + __uint_as_float(m[3].x));
            const float f1 = (__uint_as_float(m[0].y) + __uint_as_float(m[1].y)) + (__uint_as_float(m[2].y) + __uint_as_float(m[3].y));
            const float f2 = (__uint_as_float(m[0].z) + __uint_as_float(m[1].z)) + (__uint_as_float(m[2].z) + __uint_as_float(m[3].z));
            const float f3 = (__uint_as_float(m[0].w) + __uint_as_float(m[1].w)) + (__uint_as_float(m[2].w) + __uint_as_float(m[3].w));
            uint32_t p0 = pack2(f0, f1), p1 = pack2(f2, f3);
            if (wg == 1) { p0 = pack2(1.f + bf_lo(p0), 1.f + bf_hi(p0)); p1 = pack2(1.f + bf_lo(p1), 1.f + bf_hi(p1)); }
            const int t7 = tid & 127;
            const uint32_t ta = sb + SM_T1 + (t7 >> 2) * 64 + (q & 1) * 32 + (q >> 1) * 4 + (wg ? 0 : 8);
            sts1(ta, p0); sts1(ta + 16, p1);
            __syncwarp();
            const bool o = g & 1;
            const int src = (lane & 28) | (g >> 1);
            const float sqa = __shfl_sync(~0u, o ? d[0][1] + d[2][1] : d[0][0] + d[2][0], src), ma = __shfl_sync(~0u, o ? d[0][3] + d[2][3] : d[0][2] + d[2][2], src) * (1.f / 512);
            const float sqb = __shfl_sync(~0u, o ? d[1][1] + d[3][1] : d[1][0] + d[3][0], src), mb = __shfl_sync(~0u, o ? d[1][3] + d[3][3] : d[1][2] + d[3][2], src) * (1.f / 512);
            const float ra = bf_round(rsq(fmaxf(sqa * (1.f / 512) - ma * ma, 0.f) + 1e-5f)), rb_ = bf_round(rsq(fmaxf(sqb * (1.f / 512) - mb * mb, 0.f) + 1e-5f));
            r2a = pack2(ra, ra); r2b = pack2(rb_, rb_); n2a = pack2(-ma * ra, -ma * ra); n2b = pack2(-mb * rb_, -mb * rb_);
            bar_sync(2, 320);
        }
        Ring rg;
        constexpr uint32_t d0 = SM_BASE >> 4;
        const uint32_t rel = mapa(sb + B_EMPTY, lane & 1);
        const uint32_t stg = sb + SM_A + 65536 + wg * 32768;
        float* kvg = (float*)(scr + G_KV + ((epoch & 1) * 8 + j) * 12288);
        uint32_t f[32];
        {
            float ka[32], va[32];
            uint32_t prev = 0, prev2 = 0;
            auto modulate = [&](int c) {
#pragma unroll
                for (int i = 0; i < 4; i++) {
                    uint32_t t[4];
                    lds4(t, sb + SM_T1 + (c * 4 + i) * 64 + q * 16);
                    uint32_t* r = a[c * 4 + i];
                    const uint32_t r1 = r[1];
                    r[0] = hfma2(hfma2(r[0], r2a, n2a), t[0], t[2]); r[1] = hfma2(hfma2(r[2], r2b, n2b), t[0], t[2]);
                    r[2] = hfma2(hfma2(r1, r2a, n2a), t[1], t[3]);   r[3] = hfma2(hfma2(r[3], r2b, n2b), t[1], t[3]);
                }
                pin<16>(&a[c * 4][0]);
            };
#pragma unroll
            for (int s = 0; s < 8; s++) {
                modulate(s);
                if (s > 1) { wg_wait<1>(); if (lane < 2) mbar_arrive_cl(rel + prev2 * 8); }
                mbar_wait(sb + B_FULL + rg.s * 8, rg.ph);
                const uint64_t d = desc(d0, SM_RING + rg.s * 16384);
                wg_fence();
#pragma unroll
                for (int k = 0; k < 4; k++) {
                    if (s + k) { if (s < 7) wg_rs64(ka, a[s * 4 + k], d + k * 128); wg_rs64(va, a[s * 4 + k], d + 512 + k * 128); }
                    else { wg_rs64z(ka, a[0], d); wg_rs64z(va, a[0], d + 512); }
                }
                wg_commit();
                if (s == 7) {
#pragma unroll
                    for (int k = 0; k < 4; k++) wg_rs64(ka, a[28 + k], d + k * 128);
                    wg_commit();
                }
                prev2 = prev; prev = rg.s; rg.skip();
            }
            wg_wait<1>(); pin<32>(va);
#pragma unroll
            for (int h = 0; h < 4; h++) {
                uint32_t vb[4];
#pragma unroll
                for (int i = 0; i < 4; i++) vb[i] = pack2(va[8 * h + 2 * i], va[8 * h + 2 * i + 1]);
                stsm4(stg + 16384 + (h >> 1) * 8192 + (w4 * 16 + lrow) * 128 + ((((h & 1) * 2 + lu) ^ lx) << 4), vb);
            }
            wg_wait<0>(); pin<32>(ka);
            if (lane < 2) { mbar_arrive_cl(rel + prev2 * 8); mbar_arrive_cl(rel + prev * 8); }
            uint32_t kb[16];
#pragma unroll
            for (int i = 0; i < 16; i++) kb[i] = pack2(ka[2 * i], ka[2 * i + 1]);
            pin<16>(kb);
            float pk[32];
            wg_fence();
#pragma unroll
            for (int h = 0; h < 4; h++) { if (h) wg_rs64(pk, kb + 4 * h, desc(d0, SM_WPHI) + h * 128); else wg_rs64z(pk, kb, desc(d0, SM_WPHI)); }
            wg_commit();
            const uint32_t ones[4] = {0x3F803F80u, 0x3F803F80u, 0x3F803F80u, 0x3F803F80u};
            sts4(stg + 16384 + lu * 8192 + (w4 * 16 + lrow) * 128 + ((4 ^ lx) << 4), ones);
            wg_wait<0>(); pin<32>(pk);
            feature_map<true>(pk, f, epoch >> 2);
#pragma unroll
            for (int r = 0; r < 2; r++)
#pragma unroll
                for (int i = 0; i < 4; i++) {
                    const uint32_t v[4] = {f[8 * i + r], f[8 * i + 2 + r], f[8 * i + 4 + r], f[8 * i + 6 + r]};
                    sts4(stg + (q >> 1) * 8192 + (w4 * 16 + g + r * 8) * 128 + ((((q & 1) * 4 + (i ^ (q & 2))) ^ g) << 4), v);
                }
            fence_async_smem();
            bar_sync(8, 256);
        }
        float qa[32];
        auto q_group = [&](int s) {
            mbar_wait(sb + B_QFULL + s * 8, 0);
            const uint64_t d = desc(d0, SM_A + s * 16384);
            wg_fence();
#pragma unroll
            for (int k = 0; k < 8; k++) { if (s + k) wg_rs64(qa, a[s * 8 + k], d + k * 128); else wg_rs64z(qa, a[0], d); }
        };
        {
            float kv[20];
            const uint64_t d = desc(d0, SM_A + 65536 + wg * 8192);
            wg_fence();
#pragma unroll
            for (int k = 0; k < 8; k++) {
                const uint64_t dk = d + (k >> 2) * 2048 + (k & 3) * 128;
                if (k) wg_ss40(kv, dk, dk + 1024); else wg_ss40z(kv, dk, dk + 1024);
            }
            wg_commit();
            wg_wait<0>(); pin<20>(kv);
            if (lane < 2) mbar_arrive(sb + B_PUBKV);
            const bool hi = w4 & 2;
            float v[9];
#pragma unroll
            for (int i = 0; i < 8; i++) v[i] = hi ? kv[8 + i] : kv[i];
            v[8] = q & 1 ? kv[18] : kv[16];
#pragma unroll
            for (int i = 0; i < 3; i++)
                asm volatile("red.relaxed.gpu.global.add.v4.f32 [%0], {%1,%2,%3,%4};" :: "l"(kvg + ((warp ^ wg) * 3 + i) * 128 + lane * 4),
                    "f"(v[3 * i]), "f"(v[3 * i + 1]), "f"(v[3 * i + 2]), "f"(1.f) : "memory");
        }
        uint4 c[6];
        uint32_t ad, adz;
#pragma unroll
        for (int i = 0; i < 6; i++) c[i].w = 0;
        {
            if (wg == 1) {
                mbar_wait(sb + B_FULL + 4 * 8, 1);
                float v[8] = {0.f, 0.f, 0.f, 0.f, 0.f, 0.f, 0.f, 0.f};
#pragma unroll 1
                for (int i0 = 0; i0 < 8; i0 += GU) {
                    uint32_t w[GU][4]; float sc[GU];
#pragma unroll
                    for (int i = 0; i < GU; i++) { lds4(w[i], sb + SM_WM - 2048 + (i0 + i) * 2048 + tid * 16); sc[i] = lds1f(sb + SM_SC - 256 + (i0 + i) * 256 + (tid >> 1) * 4); }
#pragma unroll
                    for (int i = 0; i < GU; i++)
#pragma unroll
                        for (int e = 0; e < 4; e++) { v[2 * e] = fmaf(bf_lo(w[i][e]), sc[i], v[2 * e]); v[2 * e + 1] = fmaf(bf_hi(w[i][e]), sc[i], v[2 * e + 1]); }
                }
                sts1(sb + SM_RED + w4 * 128 + lane * 4, __float_as_uint(tsum8(v, lane)));
                __syncwarp();
                if (lane < 4) { mbar_arrive(sb + B_AFREE); mbar_arrive_cl(rel + 4 * 8); }
                bar_sync(3, 256);
            }
            rg.next();
#pragma unroll
            for (int s = 0; s < 4; s++) q_group(s);
            wg_commit();
            if (wg == 0) bar_arrive(3, 256);
            wg_wait<0>(); pin<32>(qa);
            if (lane < 2) mbar_arrive(sb + B_QDONE);
            uint32_t kb[16];
#pragma unroll
            for (int i = 0; i < 16; i++) kb[i] = pack2(qa[2 * i], qa[2 * i + 1]);
            pin<16>(kb);
            float pq[32];
            wg_fence();
#pragma unroll
            for (int h = 0; h < 4; h++) { if (h) wg_rs64(pq, kb + 4 * h, desc(d0, SM_WPHI) + h * 128); else wg_rs64z(pq, kb, desc(d0, SM_WPHI)); }
            wg_commit(); wg_wait<0>(); pin<32>(pq);
            ad = sb + SM_KV + (g >> 1) * 1440 + q * 160 + w4 * 36 + (g & 1) * 16; adz = ad + q * (5760 - 160) + 1280;
            pin<1>(&ad); pin<1>(&adz);
            feature_map<false, 0, 1>(pq, f, epoch >> 2);
            if (wg == 0) {
#pragma unroll
                for (int i = 0; i < 6; i++) c[i] = ld_rlx4(kvg + (w4 * 6 + i) * 128 + lane * 4);
            }
            feature_map<false, 1, 2>(pq, f, epoch >> 2);
        }
        const uint32_t zone = sb + SM_A + wg * 65536 + w4 * 2048 + lane * 16;
        const uint32_t toff = (w4 * 16 + g) * 128 + ((q ^ g) << 4);
        unsigned char* xg = rs + G_O + wg * 65536;
        Tag tg = {(uint32_t)(~lane & 1), epoch & ~lane & 1};
        asm volatile("" : "+r"(tg.tm), "+r"(tg.tp));
        unsigned char* hint = rs + G_FL2 + (wg * 8 + j) * 16 + w4 * 4;
        uint32_t xr[16];
        {
            if (wg == 0) {
#pragma unroll 1
                for (;;) {
                    if (!__any_sync(~0u, (c[0].w & c[1].w & c[2].w & c[3].w & c[4].w & c[5].w) != 0x41800000u)) break;
#pragma unroll
                    for (int i = 0; i < 6; i++) c[i] = ld_rlx4(kvg + (w4 * 6 + i) * 128 + lane * 4);
                }
                mbar_wait(sb + B_KVZ, 0);
#pragma unroll
                for (int ks = 0; ks < 2; ks++) {
                    const uint4 c0_ = c[3 * ks], c1_ = c[3 * ks + 1], c2_ = c[3 * ks + 2];
                    sts1(ad + ks * 11520, pack2(__uint_as_float(c0_.x), __uint_as_float(c0_.y)));
                    sts1(ad + ks * 11520 + 5760, pack2(__uint_as_float(c0_.z), __uint_as_float(c1_.x)));
                    sts1(ad + ks * 11520 + 640, pack2(__uint_as_float(c1_.y), __uint_as_float(c1_.z)));
                    sts1(ad + ks * 11520 + 5760 + 640, pack2(__uint_as_float(c2_.x), __uint_as_float(c2_.y)));
                    if (q < 2) sts1(adz + ks * 11520, pack2(__uint_as_float(c2_.z), 1.f));
                }
                fence_async_smem();
                bar_sync(4, 128);
            } else bar_sync(9, 256);
            float ap[36], an[36];
            pin<32>(f);
            wg_fence();
#pragma unroll
            for (int s = 0; s < 8; s++) {
                const uint64_t d = desc(d0, SM_KV, 1440, 10) + s * 180;
                if (s & 3) wg_rs72(s < 4 ? ap : an, f + 4 * s, d); else wg_rs72z(s < 4 ? ap : an, f + 4 * s, d);
            }
            wg_commit();
            mbar_wait(sb + B_AUX, 0);
#pragma unroll
            for (int k = 0; k < 4; k++) ldsm4(xr + 4 * k, sb + SM_XS + (warp * 16 + lrow) * 128 + (((k * 2 + lu) ^ lx) << 4));
            wg_wait<0>(); pin<36>(ap); pin<36>(an);
            if (lane < 2) mbar_arrive(sb + B_OFREE);
            float cp[2], cn[2];
#pragma unroll
            for (int r = 0; r < 2; r++) {
                const float sp = ap[33 + 2 * r], sn = an[33 + 2 * r];
                const float id = rcp(fmaf(fmaf(sp, 1e-6f, ap[32 + 2 * r]), sn, an[32 + 2 * r] * sp));
                cp[r] = sn * id; cn[r] = sp * id;
            }
            uint32_t o[4][4];
#pragma unroll
            for (int c = 0; c < 4; c++)
#pragma unroll
                for (int t = 0; t < 4; t++) {
                    const int e = (c >> 1) * 16 + t * 4 + (c & 1) * 2;
                    o[c][t] = pack2(fmaf(ap[e], cp[c & 1], an[e] * cn[c & 1]), fmaf(ap[e + 1], cp[c & 1], an[e + 1] * cn[c & 1]));
                }
            tile_tag(o, tg);
            if (wg == 0) { pin<16>(&o[0][0]); bar_arrive(9, 256); }
#pragma unroll
            for (int c = 0; c < 4; c++) stg4(xg + j * 8192 + ((toff ^ ((c >> 1) * 64)) + (c & 1) * 1024), o[c]);
            if (lane == 0) st_rlx(hint, epoch);
            mbar_wait(sb + (wg ? B_OFREE : B_QDONE), 0);
#pragma unroll
            for (int c = 0; c < 4; c++) sts4(sb + SM_A + wg * 65536 + (toff ^ ((c >> 1) * 64)) + (c & 1) * 1024, o[c]);
            fence_async_smem();
            bar_sync(4 + wg, 128);
        }
        float acc[32], xf[32], ga[16], gs[8][4];
#pragma unroll
        for (int i = 0; i < 16; i++) { xf[2 * i] = bf_lo(xr[i]); xf[2 * i + 1] = bf_hi(xr[i]); }
        mbar_wait(sb + B_MOD2, 0);
#pragma unroll
        for (int nt = 0; nt < 8; nt++) {
            lds2f(ga + 2 * nt, sb + SM_GAB + nt * 32 + q * 8);
            lds2f(gs[nt], sb + SM_GAB + 512 + nt * 32 + q * 8); lds2f(gs[nt] + 2, sb + SM_GAB + 256 + nt * 32 + q * 8);
        }
        pin<32>(xf);
        {
            const uint64_t da = desc(d0, SM_A + wg * 65536);
#pragma unroll
            for (int s = 0; s < 4; s++) mbar_wait(sb + B_FULL + (s + 5) % NST * 8, s == 0);
#pragma unroll
            for (int i = 0; i < 8; i++) {
                if (i == 1) tiles_ready<WB1 - 1>(sb + B_LAND + wg * 64, 0, 1, sb + SM_A + wg * 65536 + w4 * 2048, xg + w4 * 2048, j, lane, epoch);
                if (i == WB1) tiles_ready<8 - WB1>(sb + B_LAND + wg * 64, 0, WB1, sb + SM_A + wg * 65536 + w4 * 2048, xg + w4 * 2048, j, lane, epoch);
                const uint64_t d = desc(d0, SM_RING + ((i >> 1) + 5) % NST * 16384 + (i & 1) * 8192);
                wg_fence();
#pragma unroll
                for (int k = 0; k < 4; k++) { if (i + k) wg_ss64(acc, da + i * 512 + k * 2, d + k * 128); else wg_ss64z(acc, da, d); }
                wg_commit();
                if (((GM >> i) & 1) && wg == 1) wg_wait<0>();
            }
            wg_wait<0>(); pin<32>(acc);
            if (lane < 4) mbar_arrive(sb + B_ZFREE + wg * 8);
            if (lane < 8) mbar_arrive_cl(rel + (lane < 2 ? 5 : (lane >> 1) - 1) * 8);
            rg.s = 3; rg.ph = 0;
        }
        {
            float st[8] = {0.f, 0.f, 0.f, 0.f, 0.f, 0.f, 0.f, 0.f};
#pragma unroll
            for (int i = 0; i < 32; i++) {
                xf[i] = fmaf(ga[(i >> 2) * 2 + (i & 1)], acc[i], xf[i]);
                st[i & 3] += xf[i]; st[4 + (i & 3)] = fmaf(xf[i], xf[i], st[4 + (i & 3)]);
            }
            unsigned char* stp = rs + G_STAT + warp * 1024 + lane * 4;
            st_rlx(stp + j * 128, (__float_as_uint(quad_tsum(st[0] + st[1], st[4] + st[5], st[2] + st[3], st[6] + st[7], q)) & ~3u) | tag);
#pragma unroll
            for (int i = 0; i < 16; i++) xr[i] = pack2(xf[2 * i], xf[2 * i + 1]);
            pin<16>(xr);
            uint32_t m[8];
#pragma unroll
            for (int i = 0; i < 32; i++) xf[i] *= gs[i >> 2][i & 1];
            pin<32>(xf);
#pragma unroll 1
            while (true) {
                uint32_t bad = 0;
#pragma unroll
                for (int i = 0; i < 8; i++) m[i] = ld_rlx(stp + i * 128);
#pragma unroll
                for (int i = 0; i < 8; i++) bad |= m[i] ^ tag;
                if (!__any_sync(~0u, bad & 3)) break;
            }
            const float t = (((__uint_as_float(m[0]) + __uint_as_float(m[1])) + (__uint_as_float(m[2]) + __uint_as_float(m[3]))) + ((__uint_as_float(m[4]) + __uint_as_float(m[5])) + (__uint_as_float(m[6]) + __uint_as_float(m[7])))) * (1.f / 512);
            const float ma = __shfl_sync(~0u, t, 0, 4), ea = __shfl_sync(~0u, t, 1, 4), mb = __shfl_sync(~0u, t, 2, 4), eb = __shfl_sync(~0u, t, 3, 4);
            const float ra = rsq(fmaxf(ea - ma * ma, 0.f) + 1e-5f), rb_ = rsq(fmaxf(eb - mb * mb, 0.f) + 1e-5f);
            const float na = -ma * ra, nb = -mb * rb_;
            uint32_t h2[4][4];
#pragma unroll
            for (int c = 0; c < 4; c++)
#pragma unroll
                for (int t = 0; t < 4; t++) {
                    const float* t2 = gs[(c >> 1) * 4 + t];
                    const float r = c & 1 ? rb_ : ra, nn = c & 1 ? nb : na;
                    const float* x = xf + (c >> 1) * 16 + 4 * t + (c & 1) * 2;
                    h2[c][t] = pack2(fmaf(x[0], r, fmaf(nn, t2[0], t2[2])), fmaf(x[1], r, fmaf(nn, t2[1], t2[3])));
                }
            tile_tag(h2, tg);
            if (wg == 1) bar_sync(3, 256);
#pragma unroll
            for (int c = 0; c < 4; c++) stg4(xg + 131072 + j * 8192 + ((toff ^ ((c >> 1) * 64)) + (c & 1) * 1024), h2[c]);
            if (lane == 0) st_rlx(hint + 256, epoch);
            if (wg == 0) bar_arrive(3, 256);
#pragma unroll
            for (int c = 0; c < 4; c++) sts4(sb + SM_A + wg * 65536 + (toff ^ ((c >> 1) * 64)) + (c & 1) * 1024, h2[c]);
            fence_async_smem();
            bar_sync(4 + wg, 128);
        }
        unsigned char* hint4 = rs + G_FL4 + (wg * 8 + j) * 16 + w4 * 4;
        uint32_t hh[14][4], hp[14][4];
        unsigned char* hg = rs + G_HH + warp * 4096 + lane * 16;
        {
            float big[128];
            ffn1_pass<256>(big, sb, rg, rel, xg + 131072, nullptr, nullptr, nullptr, epoch, wg, w4, j, lane);
#pragma unroll
            for (int i = 0; i < 32; i++) (&hh[0][0])[i] = reglu2(big[2 * i], big[2 * i + 1], big[64 + 2 * i], big[65 + 2 * i]);
#pragma unroll
            for (int k = 0; k < 8; k++) set_tag(hh[k], tg);
            pin<32>(&hh[0][0]);
        }
        {
            float big[96];
            ffn1_pass<192>(big, sb, rg, rel, hg + (j ^ 1) * 57344, hp, hh, hg + j * 57344, 0, wg, w4, j, lane);
            if (lane < 4) mbar_arrive(sb + B_ZFREE + wg * 8);
#pragma unroll
            for (int i = 0; i < 24; i++) (&hh[8][0])[i] = reglu2(big[2 * i], big[2 * i + 1], big[48 + 2 * i], big[49 + 2 * i]);
#pragma unroll
            for (int k = 8; k < 14; k++) set_tag(hh[k], tg);
            pin<24>(&hh[8][0]);
        }
        unsigned char* pg = rs + G_P + wg * 8192 + w4 * 2048 + lane * 16;
        uint32_t snd[8][4];
        rg.s = 5; rg.ph = 1;
        {
            float y2[64];
            uint32_t prev = 0;
#pragma unroll
            for (int s = 0; s < 8; s++) {
                if (s == 2) ldg_recheck<8>(hp, hg + (j ^ 1) * 57344, tg);
                if (s == 6) {
                    mbar_waitc(sb + B_LAND + (wg * 8 + 4) * 8, 0);
                    lds_checked<6>(hp + 8, zone + 4 * 8192 + w4 * 1024,
                                   hg + (j ^ 1) * 57344 + 32768 - warp * 1024, tg);
                }
                mbar_waitc(sb + B_FULL + rg.s * 8, rg.ph);
                const uint64_t d = desc(d0, SM_RING + rg.s * 16384, s < 4 ? 8192 : 6144);
                uint32_t (*h)[4] = (s & 2 ? hp : hh) + (s < 4 ? (s & 1) * 4 : 8 + (s & 1) * 3);
                wg_fence();
#pragma unroll
                for (int k = 0; k < (s < 4 ? 4 : 3); k++) { if (s + k) wg_rs128(y2, h[k], d + k * 128); else wg_rs128z(y2, h[k], d); }
                wg_commit();
                if (s < 2) {
#pragma unroll
                    for (int k = 3 * s; k < 3 * s + 3; k++) stg4(hg + j * 57344 + 32768 - warp * 1024 + k * 512, hh[8 + k]);
                    if (s == 1 && lane == 0) st_rlx(hint4 + (j ^ 1) * 256, epoch);
                }
                if (s == 2) {
#pragma unroll
                    for (int k = 0; k < 4; k++) sts4(zone + k * 512, xr + 4 * k);
                }
                if (s > 0) { wg_wait<1>(); if (lane < 2) mbar_arrive_cl(rel + prev * 8); }
                prev = rg.s; rg.next();
            }
            wg_wait<0>(); pin<64>(y2);
            if (lane < 2) mbar_arrive_cl(rel + prev * 8);
#pragma unroll
            for (int i = 0; i < 32; i++) (&snd[0][0])[i] = pack2(y2[2 * i], y2[2 * i + 1]);
            pin<32>(&snd[0][0]);
        }
        float y[32];
        uint32_t pa[4][4], pb[4][4], gb[8];
        auto fetch = [&](uint32_t (*v)[4], int ns) {
            mbar_waitc(sb + B_LAND + (wg * 8 + 1 + ns) * 8, 0);
#pragma unroll
            for (int k = 0; k < 4; k++) lds4(v[k], zone + (1 + ns) * 8192 + k * 512);
        };
        auto check = [&](uint32_t (*v)[4], int ns) { ldg_recheck<4>(v, pg + (j * 4 + (((j + 6 - 2 * ns) & 7) >> 1)) * 16384, tg); };
        auto ship = [&](int cc, int k) {
            const int dst = (j + 2 + (k >> 2) * 2 + 4 * cc) & 7;
            stg_tagged(pg + (dst * 4 + (j >> 1)) * 16384 + (k & 3) * 512, snd[k], tg);
            if ((k & 3) == 3 && lane == 0) st_rlx(hint4 + dst * 256, epoch);
        };
#pragma unroll
        for (int cc = 0; cc < 2; cc++) {
            uint32_t prev = 0;
            ship(cc, 0); ship(cc, 1);
#pragma unroll
            for (int s = 0; s < 4; s++) {
                mbar_waitc(sb + B_FULL + rg.s * 8, rg.ph);
                const uint64_t d = desc(d0, SM_RING + rg.s * 16384);
                uint32_t (*h)[4] = (s < 2 ? hh : hp) + (s & 1) * 8;
                wg_fence();
#pragma unroll
                for (int k = 0; k < (s & 1 ? 6 : 8); k++) { if (s + k) wg_rs64(y, h[k], d + k * 128); else wg_rs64z(y, h[k], d); }
                wg_commit();
#pragma unroll
                for (int k = 2 * s + 2; k < 2 * s + 4; k++) if (k < (cc ? 4 : 8)) ship(cc, k);
                if (cc == 0 && (s == 1 || s == 2)) { wg_wait<1>(); if (lane < 2) mbar_arrive_cl(rel + prev * 8); }
                if (cc == 1 && s == 2) fetch(pa, 0);
                if (cc == 1 && s == 1) {
#pragma unroll
                    for (int k = 0; k < 4; k++) lds4(xr + 4 * k, zone + k * 512);
#pragma unroll
                    for (int nt = 0; nt < 8; nt++) { float t[2]; lds2f(t, sb + SM_GAB + 768 + nt * 32 + q * 8); gb[nt] = __byte_perm(__float_as_uint(t[0]), __float_as_uint(t[1]), 0x7632); }
                }
                if (cc == 1 && s == 3) {
                    fetch(pb, 1); check(pa, 0); check(pb, 1);
#pragma unroll
                    for (int i = 0; i < 16; i++) (&pa[0][0])[i] = hadd2((&pa[0][0])[i], (&pb[0][0])[i]);
                }
                prev = rg.s; rg.next();
            }
            wg_wait<0>(); pin<32>(y);
            if (cc == 0) {
#pragma unroll
                for (int i = 0; i < 16; i++) (&snd[0][0])[i] = pack2(y[2 * i], y[2 * i + 1]);
                pin<16>(&snd[0][0]);
            }
        }
        {
            const uint32_t ob = sb + SM_A + wg * 65536 + 6 * 8192 + w4 * 2048;
#pragma unroll
            for (int i = 0; i < 16; i++) (&pa[0][0])[i] = hadd2(pack2(y[2 * i], y[2 * i + 1]), (&pa[0][0])[i]);
            pin<16>(&pa[0][0]);
            fetch(pb, 2); check(pb, 2);
            if (lane < 2) mbar_arrive(sb + B_DONE);
#pragma unroll
            for (int k = 0; k < 4; k++) {
#pragma unroll
                for (int i = 0; i < 4; i++) pb[k][i] = hfma2(gb[2 * k + (i >> 1)], hadd2(pa[k][i], pb[k][i]), xr[4 * k + i]);
                stsm4(ob + lrow * 128 + (((k * 2 + lu) ^ lx) << 4), pb[k]);
            }
            __syncwarp();
#pragma unroll
            for (int i = 0; i < 4; i++) {
                const int r = i * 4 + (lane >> 3);
                uint32_t w[4];
                lds4(w, ob + r * 128 + ((lx ^ (r & 7)) << 4));
                stg4(out + (size_t)(rb * 128 + warp * 16 + r) * 512 + j * 64 + lx * 8, w);
            }
        }
    } else {
        if (warp == 9 && elect()) {
#pragma unroll
            for (int i = 0; i < 8; i++) {
                mbar_expect(sb + B_X + i * 8, 16384);
                tma3d(sb + SM_A + (i & 1) * 65536 + (i >> 1) * 16384, &maps.x, 0, rb * 128 + (i & 1) * 64, i & 6, sb + B_X + i * 8);
            }
        }
        if (warp == 8 && elect()) tmap_prefetch(&maps.qkv);
        asm volatile("setmaxnreg.dec.sync.aligned.u32 40;");
        asm volatile("barrier.cluster.wait.aligned;" ::: "memory");
        if (warp == 8) {
            const uint2 e0 = ldg_nc2(&sched->e[j * 2 + rank][lane]), e1 = ldg_nc2(&sched->e[j * 2 + rank][lane + 32]);
            while ((uint32_t)clock() - t0 < WDELAY) {}
#pragma unroll 1
            for (int n = 0; n < 64; n++) {
                const uint32_t ex = __shfl_sync(~0u, n < 32 ? e0.x : e1.x, n), ey = __shfl_sync(~0u, n < 32 ? e0.y : e1.y, n);
                const uint32_t fb = sb + SM_BAR + ((ex >> 10) & 511);
                mbar_wait(sb + SM_BAR + (ex & 511), (ex >> 9) & 1);
                if (elect()) {
                    mbar_expect(fb, ex & (1 << 19) ? 12288 : 16384);
                    tma5d_mc(sb + (ex >> 24) * 2048, &maps.qkv + ((ex >> 20) & 15), ey & 2047, (ey >> 11) & 2047, ey >> 22, fb);
                }
            }
        } else if (warp < 11) {
            const int wg = warp - 9;
            uint32_t epoch;
            {
                const int t = tid - 288, k = t >> 2;
                uint2 wph[4]; uint32_t cw[4];
#pragma unroll
                for (int h = 0; h < 4; h++) { wph[h] = ldg_nc2(wphi + j * 1024 + h * 256 + t * 4); cw[h] = ldg_nc(cvec + h * 128 + t * 2); }
#pragma unroll
                for (int h = 0; h < 4; h++) {
                    const uint32_t ad = sb + SM_WPHI + h * 2048 + k * 128 + ((((t & 3) * 2) ^ (k & 7)) << 4);
                    sts_word(ad, wph[h].x, h); sts_word(ad ^ 16, wph[h].y, h);
                    sts2(sb + SM_SC + h * 512 + t * 8, __float_as_uint(silu_bf(cw[h] & 0xFFFF)), __float_as_uint(silu_bf(cw[h] >> 16)));
                }
                fence_async_smem();
                bar_arrive(2, 320);
            }
            {
                mbar_wait(sb + B_PUBKV, 0);
                epoch = __float_as_uint(lds1f(sb + SM_EPO));
                const uint32_t z[4] = {0, 0, 0, 0};
#pragma unroll 2
                for (int i = 0; i < 24; i++) sts4(sb + SM_KV + wg * 12288 + i * 512 + lane * 16, z);
                fence_async_smem();
                __syncwarp();
                if (lane < 8) mbar_arrive(sb + B_KVZ);
            }
            const int p = lane >> 2, sub = lane & 3;
#pragma unroll 1
            for (int e0 = 0; e0 < 4; e0++) {
                const int e = (e0 + 1) >> 1;
                const bool hh2 = e == 2 && p == (j ^ 1);
                uint32_t todo = __ballot_sync(~0u, sub == 0 && p != j && (e == 1 ? (p + (p < j) > NB) == (e0 == 2) : e == 0 || hh2 || !((p ^ j) & 1)));
                const unsigned char* fp = rs + (e < 2 ? G_FL2 + e * 256 : G_FL4 + j * 256) + wg * 128 + lane * 4;
                const unsigned char* src = rs + (e < 2 ? G_O + e * 131072 + (wg * 8 + p) * 8192 : hh2 ? G_HH + p * 57344 + 32768 + wg * 12288 : G_P + ((j * 4 + (p >> 1)) * 2 + wg) * 8192);
                const uint32_t slot = wg * 8 + (e < 2 ? p + (p < j) : hh2 ? 4 : ((j - p) & 7) >> 1), bytes = hh2 ? 12288 : 8192;
                const uint32_t lb = sb + B_LAND + slot * 8;
                auto look = [&](uint32_t f) {
                    uint32_t r = __ballot_sync(~0u, f == epoch);
                    r &= r >> 1; r &= r >> 2;
                    if (e < 2 && (r & 0x11111111u) != 0x11111111u) r = 0;
                    r &= todo;
                    if ((r >> lane) & 1) { mbar_expect(lb, bytes); bulk_load(sb + SM_A + slot * 8192, src, bytes, lb); }
                    todo ^= r;
                };
                uint32_t f0 = ld_rlx(fp);
                mbar_wait(sb + (e0 == 2 ? B_LAND + 9 * 8 : e > 0 ? B_ZFREE + wg * 8 : wg ? B_OFREE : B_QDONE), e0 >> 1);
#pragma unroll 1
                for (;;) { look(f0); if (!todo) break; f0 = ld_rlx(fp); }
            }
        } else {
            const uint32_t epoch = (ep0 + 1) & 3;
            if (lane == 0) { sts1(sb + SM_EPO, epoch); mbar_arrive(sb + B_EPO); }
            bar_sync(1, 288);
            {
                float s = 0.f;
#pragma unroll
                for (int i = 0; i < 8; i++) s += lds1f(sb + SM_RED + i * 128 + lane * 4);
                st_rlx(scr + G_MOD1 + (b & 3) * 4096 + ((b >> 2) * 32 + lane) * 4, (__float_as_uint(s) & ~3u) | epoch);
            }
            if (lane < 9) tmap_prefetch(&maps.wo + lane);
            const char* pf = lane == 0 ? (const char*)wqkv + b * 12288 : lane < 5 ? (const char*)wmod + (size_t)(b + 128 * (lane - 1)) * 6144 + 2048
                           : lane == 5 ? (const char*)wo + b * 4096 : (lane == 6 ? (const char*)wgate : lane == 7 ? (const char*)wup : (const char*)wdown) + b * 14336;
            mbar_watch(sb + B_X + PF1);
            if (lane == 0) l2_prefetch(pf, 12288);
            mbar_watch(sb + B_XFREE);
            if (lane >= 1 && lane < 6) l2_prefetch(pf, 4096);
            {
                const uint32_t z[4] = {0, 0, 0, 0};
                unsigned char* zp = scr + G_KV + (((epoch + 1) & 1) * 8 + j) * 12288 + rb * 768;
                stg4(zp + lane * 16, z);
                if (lane < 16) stg4(zp + 512 + lane * 16, z);
            }
            unsigned char* m2p = scr + G_MOD2 + (b * 16 + (lane & 1) * 8 + (lane >> 2)) * 4;
            if (!(lane & 2)) st_rlx(m2p, epoch ^ 2);
            mbar_watch(sb + B_EMPTY + 4 * 8);
            if (elect()) {
                mbar_expect(sb + B_FULL + 4 * 8, 16384);
                tma2d(sb + SM_WM, &maps.wm, 1024 + b * 16, 0, sb + B_FULL + 4 * 8);
                tma2d(sb + SM_WM + 8192, &maps.wm, 1024 + b * 16, 256, sb + B_FULL + 4 * 8);
            }
            mbar_watch(sb + B_PUBKV);
            if (elect()) { mbar_expect(sb + B_AUX, 16384); tma2d(sb + SM_XS, &maps.xs, j * 64, rb * 128, sb + B_AUX); }
            mbar_watch(sb + B_AFREE);
            float t = 0.f;
#pragma unroll
            for (int i = 0; i < 4; i++) t += lds1f(sb + SM_RED + i * 128 + lane * 4);
            t += __shfl_xor_sync(~0u, t, 2);
            if (!(lane & 2)) st_rlx(m2p, (pack2(0.f, t) & 0xFFFF0000u) | epoch);
            uint4 m[2];
#pragma unroll 1
            for (int n = 0; n < SPIN_LIMIT; n++) {
                uint32_t bad = 0;
#pragma unroll
                for (int i = 0; i < 2; i++) {
                    m[i] = ld_rlx4(scr + G_MOD2 + ((i * 2 + (lane >> 4)) * 512 + j * 64 + (lane & 15) * 4) * 4);
                    bad |= (m[i].x ^ epoch) | (m[i].y ^ epoch) | (m[i].z ^ epoch) | (m[i].w ^ epoch);
                }
                if (!__any_sync(~0u, bad & 3)) break;
            }
#pragma unroll
            for (int i = 0; i < 2; i++) {
                uint32_t w[4] = {m[i].x & 0xFFFF0000u, m[i].y & 0xFFFF0000u, m[i].z & 0xFFFF0000u, m[i].w & 0xFFFF0000u};
                if (i == 1 && lane < 16) {
#pragma unroll
                    for (int e = 0; e < 4; e++) w[e] = __float_as_uint(bf_round(1.f + __uint_as_float(w[e])));
                }
                sts4(sb + SM_GAB + i * 512 + lane * 16, w);
            }
            __syncwarp();
            if (lane < 16) mbar_arrive(sb + B_MOD2);
            if (lane == 6 || lane == 7) l2_prefetch(pf, 14336);
            mbar_watch(sb + B_OFREE);
            if (lane < 16) mbar_arrive_cl(mapa(sb + B_MFREE, lane & 1));
            mbar_watch(sb + B_ZFREE + 8);
            mbar_watch(sb + B_LAND + 15 * 8, 1);
            if (lane == 8) l2_prefetch(pf, 14336);
            mbar_watch(sb + B_DONE);
        }
    }
}

typedef CUresult (*EncodeFn)(CUtensorMap*, CUtensorMapDataType, cuuint32_t, void*, const cuuint64_t*, const cuuint64_t*, const cuuint32_t*,
                             const cuuint32_t*, CUtensorMapInterleave, CUtensorMapSwizzle, CUtensorMapL2promotion, CUtensorMapFloatOOBfill);

void make_map(EncodeFn enc, CUtensorMap* m, const void* p, int rank, cuuint64_t d0, cuuint64_t d1, cuuint64_t d2, cuuint64_t s1, cuuint64_t s2,
              cuuint32_t b0, cuuint32_t b1, cuuint32_t b2, CUtensorMapSwizzle sw) {
    cuuint64_t dims[3] = {d0, d1, d2}, str[2] = {s1, s2};
    cuuint32_t box[3] = {b0, b1, b2}, es[3] = {1, 1, 1};
    enc(m, CU_TENSOR_MAP_DATA_TYPE_BFLOAT16, rank, const_cast<void*>(p), dims, str, box, es, CU_TENSOR_MAP_INTERLEAVE_NONE, sw,
        CU_TENSOR_MAP_L2_PROMOTION_L2_128B, CU_TENSOR_MAP_FLOAT_OOB_FILL_NONE);
}

struct U5 { cuuint64_t v[5]; };
void make_map5(EncodeFn enc, CUtensorMap* m, const void* p, U5 dims, U5 str, U5 bx, CUtensorMapSwizzle sw) {
    cuuint32_t box[5], es[5] = {1, 1, 1, 1, 1};
    for (int i = 0; i < 5; i++) box[i] = (cuuint32_t)bx.v[i];
    enc(m, CU_TENSOR_MAP_DATA_TYPE_BFLOAT16, 5, const_cast<void*>(p), dims.v, str.v, box, es, CU_TENSOR_MAP_INTERLEAVE_NONE, sw,
        CU_TENSOR_MAP_L2_PROMOTION_L2_128B, CU_TENSOR_MAP_FLOAT_OOB_FILL_NONE);
}

}

extern "C" void kernel_launch(void* const* d_in, const int* in_sizes, int n_in, void* d_out, int out_size) {
    typedef const __nv_bfloat16* P;
    P x = (P)d_in[0], wqkv = (P)d_in[1], wphi = (P)d_in[2], wo = (P)d_in[3], wg = (P)d_in[5], wu = (P)d_in[6], wd = (P)d_in[7], c = (P)d_in[8], wmod = (P)d_in[9];
    static EncodeFn enc = nullptr;
    static void* scr = nullptr;
    static void* sched = nullptr;
    if (!enc) {
        void* f = nullptr; cudaDriverEntryPointQueryResult qr;
        cudaGetDriverEntryPoint("cuTensorMapEncodeTiled", &f, cudaEnableDefault, &qr);
        enc = (EncodeFn)f;
        cudaGetSymbolAddress(&scr, g_scratch);
        scr = (void*)(((uintptr_t)scr + G_RB - 1) & ~(uintptr_t)(G_RB - 1));
        cudaGetSymbolAddress(&sched, g_sched);
        cudaFuncSetAttribute(fused_block_kernel, cudaFuncAttributeMaxDynamicSharedMemorySize, SMEM_BYTES);
    }
    Maps m;
    const CUtensorMapSwizzle S128 = CU_TENSOR_MAP_SWIZZLE_128B, S64 = CU_TENSOR_MAP_SWIZZLE_64B;
    make_map(enc, &m.x, x, 3, 64, 2048, 8, 1024, 128, 64, 64, 2, S128);
    make_map5(enc, &m.qkv, wqkv, {1536, 1, 512, 1, 1}, {3072, 3072, 3072, 3072}, {64, 1, 64, 1, 1}, S128);
    make_map5(enc, &m.wo, wo, {512, 8, 4, 2, 8}, {1024, 16 * 1024, 8 * 1024, 64 * 1024}, {64, 8, 4, 2, 1}, S128);
    make_map5(enc, &m.g1, wg, {64, 2, 64, 4, 28}, {3584, 8 * 3584, 2 * 3584, 128}, {64, 2, 4, 4, 2}, S128);
    make_map5(enc, &m.u1, wu, {64, 2, 64, 4, 28}, {3584, 8 * 3584, 2 * 3584, 128}, {64, 2, 4, 4, 2}, S128);
    make_map5(enc, &m.g2, wg, {32, 2, 64, 4, 56}, {3584, 8 * 3584, 2 * 3584, 64}, {32, 2, 4, 4, 3}, S64);
    make_map5(enc, &m.u2, wu, {32, 2, 64, 4, 56}, {3584, 8 * 3584, 2 * 3584, 64}, {32, 2, 4, 4, 3}, S64);
    make_map(enc, &m.xs, x, 2, 512, 2048, 1, 1024, 0, 64, 128, 1, S128);
    make_map(enc, &m.wm, wmod, 2, 3072, 512, 1, 6144, 0, 16, 256, 1, CU_TENSOR_MAP_SWIZZLE_NONE);
    make_map5(enc, &m.dA, wd, {512, 1, 1792, 1, 1}, {1024, 1024, 1024, 1024}, {64, 1, 64, 1, 1}, S128);
    make_map5(enc, &m.dB, wd, {512, 1, 1792, 1, 1}, {1024, 1024, 1024, 1024}, {64, 1, 48, 1, 1}, S128);

    cudaLaunchConfig_t cfg = {};
    cfg.gridDim = dim3(128); cfg.blockDim = dim3(384); cfg.dynamicSmemBytes = SMEM_BYTES; cfg.stream = cudaStreamPerThread;
    cudaLaunchAttribute at[1];
    at[0].id = cudaLaunchAttributeClusterDimension; at[0].val.clusterDim.x = 2; at[0].val.clusterDim.y = 1; at[0].val.clusterDim.z = 1;
    cfg.attrs = at; cfg.numAttrs = 1;
    cudaLaunchKernelEx(&cfg, fused_block_kernel, wmod, c, (unsigned char*)scr, wg, wphi, (__nv_bfloat16*)d_out, wqkv, wo, wu, wd, (const Sched*)sched, m);
}
```
